```python
import torch

def _softmax(x, axis=-1):
    return torch.softmax(x, dim=axis)

def _gelu(x):
    return torch.nn.functional.gelu(x, approximate='tanh')

def _silu(x):
    return torch.nn.functional.silu(x)

def _sigmoid(x):
    return torch.sigmoid(x)

def _layernorm(x, axis=-1, eps=1e-05):
    m = x.mean(dim=axis, keepdim=True)
    v = x.var(dim=axis, keepdim=True, unbiased=False)
    return (x - m) / torch.sqrt(v + eps)

def _scatter_add(tgt, idx, src, axis=0):
    return tgt.clone().index_add_(axis, idx, src)

def _segment_sum(src, seg, n):
    out = torch.zeros((n,) + src.shape[1:], dtype=src.dtype)
    return out.index_add_(0, seg, src)

def _pad(x, pw):
    flat = tuple((v for pair in reversed(pw) for v in pair))
    return torch.nn.functional.pad(x, flat)
kernel_name = 'adaLN_cond__sliding_block__dense_activation_relu__prompt'

def setup_inputs():

    _w = lambda a: (lambda t: t.to(torch.bfloat16) if t.is_floating_point() else t)(torch.as_tensor(a))

    def _A_setup():
        B, S, D = (1, 2048, 512)
        return {'x': _w((lambda *s: torch.randn(*s, dtype=torch.bfloat16) * 0.05)(B, S, D)), 'wqkv': _w((lambda *s: torch.randn(*s, dtype=torch.bfloat16) * 0.05)(D, 3 * D)), 'wo': _w((lambda *s: torch.randn(*s, dtype=torch.bfloat16) * 0.05)(D, D))}
    _A_in = _A_setup()

    def _B_setup():
        B, S, D, Dff = (1, 2048, 512, 1792)
        return {'x': _w((lambda *s: torch.randn(*s, dtype=torch.bfloat16) * 0.05)(B, S, D)), 'w1': _w((lambda *s: torch.randn(*s, dtype=torch.bfloat16) * 0.05)(D, Dff)), 'w2': _w((lambda *s: torch.randn(*s, dtype=torch.bfloat16) * 0.05)(Dff, D))}
    _B_in = _B_setup()
    return {'A_x': _A_in['x'], 'A_wqkv': _A_in['wqkv'], 'A_wo': _A_in['wo'], 'B_x': _B_in['x'], 'B_w1': _B_in['w1'], 'B_w2': _B_in['w2'], 'c': _w((lambda *s: torch.randn(*s, dtype=torch.bfloat16) * 0.1)(1, 512) * 8.0), 'w_mod': _w((lambda *s: torch.randn(*s, dtype=torch.bfloat16) * 0.1)(512, 6 * 512) * 512 ** (-0.5) * 8.0)}

def reference(A_x, A_wqkv, A_wo, B_x, B_w1, B_w2, c, w_mod):

    def _A_ref(x, wqkv, wo):
        B, S, D = x.shape
        H = 32
        Dh = D // H
        W = 256
        qkv = (lambda x, *d: x.permute(*d))((x @ wqkv).reshape(B, S, 3, H, Dh), 2, 0, 3, 1, 4)
        q, k, v = (qkv[0], qkv[1], qkv[2])
        scores = torch.einsum('bhqd,bhkd->bhqk', q, k) * Dh ** (-0.5)
        idx = torch.arange(S)
        mask = (idx[:, None] - idx[None, :] >= 0) & (idx[:, None] - idx[None, :] < W)
        scores = torch.where(mask[None, None], scores, -1000000000.0)
        p = _softmax(scores, axis=-1)
        o = torch.einsum('bhqk,bhkd->bhqd', p, v)
        return (lambda x, *d: x.permute(*d))(o, 0, 2, 1, 3).reshape(B, S, D) @ wo

    def _B_ref(x, w1, w2):
        h = torch.einsum('bsd,df->bsf', x, w1)
        zero = torch.zeros_like(h)
        h = torch.maximum(h, zero)
        return torch.einsum('bsf,fd->bsd', h, w2)
    x = A_x
    mod = (_silu(c) @ w_mod).reshape(c.shape[0], 6, 1, -1)
    sa, ca, ga, sb, cb, gb = (mod[:, 0].clone(), mod[:, 1].clone(), mod[:, 2].clone(), mod[:, 3].clone(), mod[:, 4].clone(), mod[:, 5].clone())
    h = _layernorm(x, axis=-1) * (1 + ca) + sa
    x = x + ga * _A_ref(h, A_wqkv, A_wo)
    h = _layernorm(x, axis=-1) * (1 + cb) + sb
    x = x + gb * _B_ref(h, B_w1, B_w2)
    return x
```

```cpp
#include <cuda_runtime.h>
#include <cuda_bf16.h>
#include <cuda.h>
#include <stdint.h>

#define MAPMODE 0
#define TS(n)

namespace {

constexpr int S_ = 2048, D_ = 512, DFF = 1792;
constexpr uint32_t KB = 1024;
constexpr uint32_t SM_WV = 0;
constexpr uint32_t SM_K = 64 * KB;
constexpr uint32_t SM_V = 112 * KB;
constexpr uint32_t SM_WK0 = 64 * KB, SM_WK1 = 112 * KB;
constexpr uint32_t SM_WQ = 160 * KB;
constexpr uint32_t SLOT = 28 * KB;
constexpr uint32_t SM_TAB = 224 * KB;
constexpr uint32_t SM_RED = 226 * KB;
constexpr uint32_t SM_BAR = 226 * KB + 256;
constexpr uint32_t SM_TOTAL = 227 * KB;
__device__ __forceinline__ uint32_t x_off(int c) {
  return c < 2 ? (32 + 16 * c) * KB : (c == 2 ? 96 * KB : (144 + 16 * (c - 3)) * KB);
}
enum { B_FX = 0, B_XFREE = 8, B_FW = 9  , B_EW = 15  , B_FKN = 18, B_FVN = 19,
       B_KVA = 20, B_KVB = 21, B_FWO = 22  , B_ATT = 24, B_EWO = 25, B_FS = 26  , B_ES = 34  ,
       B_TAB2 = 42, B_COUNT = 43 };

__device__ unsigned g_epoch;
__device__ uint32_t g_mod[6 * D_];
__device__ uint4 g_kv[2][16][8][8 * 4 * 32];
__device__ uint4 g_o[16][8][32][32];
__device__ uint4 g_x1[16][8][32][32];
__device__ float2 g_st[16][8][16][8];
__device__ uint4 g_part[16][8][32][8][32];
__device__ uint32_t g_fkv[2][16][8][8];
__device__ uint32_t g_fo[16][8][4][8];
__device__ uint32_t g_fx[16][8][8];
__device__ uint32_t g_fp[16][8][4][8];

__device__ __forceinline__ void mbar_init(uint32_t b, int n) { asm volatile("mbarrier.init.shared.b64 [%0], %1;" ::"r"(b), "r"(n)); }
__device__ __forceinline__ void mbar_arrive(uint32_t b) { asm volatile("mbarrier.arrive.shared.b64 _, [%0];" ::"r"(b) : "memory"); }
__device__ __forceinline__ void mbar_expect(uint32_t b, uint32_t n) { asm volatile("mbarrier.arrive.expect_tx.shared.b64 _, [%0], %1;" ::"r"(b), "r"(n) : "memory"); }
__device__ __forceinline__ void mbar_wait(uint32_t b, uint32_t parity) {
  asm volatile("{\n.reg .pred p, e;\n.reg .u32 n;\nmov.u32 n, 0;\nLW:\n"
               "mbarrier.try_wait.parity.shared.b64 p, [%0], %1;\n@p bra.uni LD;\n"
               "add.u32 n, n, 1;\nsetp.gt.u32 e, n, 4194304;\n@e trap;\nbra.uni LW;\nLD:\n}" ::"r"(b), "r"(parity) : "memory");
}
__device__ __forceinline__ void warp_arrive(uint32_t b) { __syncwarp(); if ((threadIdx.x & 31) == 0) mbar_arrive(b); }
__device__ __forceinline__ void tma2d(uint32_t dst, const CUtensorMap* tm, int c0, int c1, uint32_t bar) {
  asm volatile("cp.async.bulk.tensor.2d.shared::cluster.global.mbarrier::complete_tx::bytes [%0], [%1, {%3,%4}], [%2];"
               ::"r"(dst), "l"(tm), "r"(bar), "r"(c0), "r"(c1) : "memory");
}
__device__ __forceinline__ void tma3d(uint32_t dst, const CUtensorMap* tm, int c0, int c1, int c2, uint32_t bar) {
  asm volatile("cp.async.bulk.tensor.3d.shared::cluster.global.mbarrier::complete_tx::bytes [%0], [%1, {%3,%4,%5}], [%2];"
               ::"r"(dst), "l"(tm), "r"(bar), "r"(c0), "r"(c1), "r"(c2) : "memory");
}
__device__ __forceinline__ void bulk_ld(uint32_t dst, const void* src, uint32_t bytes, uint32_t bar) {
  asm volatile("cp.async.bulk.shared::cluster.global.mbarrier::complete_tx::bytes [%0], [%1], %2, [%3];"
               ::"r"(dst), "l"(src), "r"(bytes), "r"(bar) : "memory");
}
__device__ __forceinline__ void l2_prefetch(const void* src, uint32_t bytes) {
  asm volatile("cp.async.bulk.prefetch.L2.global [%0], %1;" ::"l"(src), "r"(bytes) : "memory");
}
__device__ __forceinline__ uint32_t ld_acq(const uint32_t* p) { uint32_t v; asm volatile("ld.acquire.gpu.global.u32 %0, [%1];" : "=r"(v) : "l"(p) : "memory"); return v; }
__device__ __forceinline__ uint32_t ld_rlx(const uint32_t* p) { uint32_t v; asm volatile("ld.relaxed.gpu.global.u32 %0, [%1];" : "=r"(v) : "l"(p) : "memory"); return v; }
__device__ __forceinline__ uint2 ld_rlx2(const void* p) { uint2 v; asm volatile("ld.relaxed.gpu.global.v2.u32 {%0,%1}, [%2];" : "=r"(v.x), "=r"(v.y) : "l"(p) : "memory"); return v; }
__device__ __forceinline__ uint4 ld_rlx4(const void* p) { uint4 v; asm volatile("ld.relaxed.gpu.global.v4.u32 {%0,%1,%2,%3}, [%4];" : "=r"(v.x), "=r"(v.y), "=r"(v.z), "=r"(v.w) : "l"(p) : "memory"); return v; }
__device__ __forceinline__ uint4 ld_nc4(const void* p) { uint4 v; asm volatile("ld.global.nc.L1::no_allocate.v4.u32 {%0,%1,%2,%3}, [%4];" : "=r"(v.x), "=r"(v.y), "=r"(v.z), "=r"(v.w) : "l"(p)); return v; }
__device__ __forceinline__ void st_rel(uint32_t* p, uint32_t v) { asm volatile("st.release.gpu.global.u32 [%0], %1;" ::"l"(p), "r"(v) : "memory"); }
__device__ __forceinline__ void st_rlx(uint32_t* p, uint32_t v) { asm volatile("st.relaxed.gpu.global.u32 [%0], %1;" ::"l"(p), "r"(v) : "memory"); }
__device__ __forceinline__ void stg4(void* p, uint32_t a, uint32_t b, uint32_t c, uint32_t d) { asm volatile("st.global.v4.u32 [%0], {%1,%2,%3,%4};" ::"l"(p), "r"(a), "r"(b), "r"(c), "r"(d) : "memory"); }
__device__ __forceinline__ void sts4(uint32_t a_, uint32_t a, uint32_t b, uint32_t c, uint32_t d) { asm volatile("st.shared.v4.u32 [%0], {%1,%2,%3,%4};" ::"r"(a_), "r"(a), "r"(b), "r"(c), "r"(d) : "memory"); }
__device__ __forceinline__ void sts1(uint32_t a_, uint32_t a) { asm volatile("st.shared.u32 [%0], %1;" ::"r"(a_), "r"(a) : "memory"); }
__device__ __forceinline__ uint4 lds4(uint32_t a) { uint4 v; asm volatile("ld.shared.v4.u32 {%0,%1,%2,%3}, [%4];" : "=r"(v.x), "=r"(v.y), "=r"(v.z), "=r"(v.w) : "r"(a) : "memory"); return v; }
__device__ __forceinline__ void warp_publish(uint32_t* flag, uint32_t tag) { __syncwarp(); if ((threadIdx.x & 31) == 0) st_rel(flag, tag); }
__device__ __forceinline__ void warp_wait_flags(const uint32_t* p, uint32_t tag) {
  asm volatile("{\n.reg .pred p, e;\n.reg .u32 n, v;\nmov.u32 n, 0;\nLW:\n"
               "ld.acquire.gpu.global.u32 v, [%0];\nsetp.eq.u32 p, v, %1;\nvote.sync.all.pred p, p, 0xffffffff;\n@p bra.uni LD;\n"
               "add.u32 n, n, 1;\nsetp.gt.u32 e, n, 4194304;\n@e trap;\nbra.uni LW;\nLD:\n}" ::"l"(p), "r"(tag) : "memory");
}
__device__ __forceinline__ uint4 wait_mod4(const uint32_t* p, uint32_t tag) {
  uint4 v;
  asm volatile("{\n.reg .pred p, e;\n.reg .u32 n, a, b;\nmov.u32 n, 0;\nLW:\n"
               "ld.relaxed.gpu.global.v4.u32 {%0,%1,%2,%3}, [%4];\n"
               "xor.b32 a, %0, %5;\nxor.b32 b, %1, %5;\nor.b32 a, a, b;\nxor.b32 b, %2, %5;\nor.b32 a, a, b;\nxor.b32 b, %3, %5;\nor.b32 a, a, b;\n"
               "and.b32 a, a, 0xffff;\nsetp.eq.u32 p, a, 0;\nvote.sync.all.pred p, p, 0xffffffff;\n@p bra.uni LD;\n"
               "add.u32 n, n, 1;\nsetp.gt.u32 e, n, 4194304;\n@e trap;\nbra.uni LW;\nLD:\n}"
               : "=&r"(v.x), "=&r"(v.y), "=&r"(v.z), "=&r"(v.w) : "l"(p), "r"(tag) : "memory");
  return v;
}
__device__ __forceinline__ uint32_t pack_bf16(float lo, float hi) { uint32_t r; asm("cvt.rn.bf16x2.f32 %0, %1, %2;" : "=r"(r) : "f"(hi), "f"(lo)); return r; }
__device__ __forceinline__ uint32_t pack_relu(float lo, float hi) { uint32_t r; asm("cvt.rn.relu.bf16x2.f32 %0, %1, %2;" : "=r"(r) : "f"(hi), "f"(lo)); return r; }
__device__ __forceinline__ uint32_t hfma2(uint32_t a, uint32_t b, uint32_t c) { uint32_t r; asm("fma.rn.bf16x2 %0, %1, %2, %3;" : "=r"(r) : "r"(a), "r"(b), "r"(c)); return r; }
__device__ __forceinline__ float bf_lo(uint32_t v) { return __uint_as_float(v << 16); }
__device__ __forceinline__ float bf_hi(uint32_t v) { return __uint_as_float(v & 0xffff0000u); }
__device__ __forceinline__ float ex2(float x) { float r; asm("ex2.approx.ftz.f32 %0, %1;" : "=f"(r) : "f"(x)); return r; }
__device__ __forceinline__ uint32_t movm(uint32_t a) { uint32_t r; asm volatile("movmatrix.sync.aligned.m8n8.trans.b16 %0, %1;" : "=r"(r) : "r"(a)); return r; }
__device__ __forceinline__ void mma16816(float (&c)[4], uint32_t a0, uint32_t a1, uint32_t a2, uint32_t a3, uint32_t b0, uint32_t b1) {
  asm("mma.sync.aligned.m16n8k16.row.col.f32.bf16.bf16.f32 {%0,%1,%2,%3}, {%4,%5,%6,%7}, {%8,%9}, {%0,%1,%2,%3};"
      : "+f"(c[0]), "+f"(c[1]), "+f"(c[2]), "+f"(c[3]) : "r"(a0), "r"(a1), "r"(a2), "r"(a3), "r"(b0), "r"(b1));
}
__device__ __forceinline__ uint64_t desc_b(uint32_t addr, uint32_t lbo, uint32_t sbo, uint32_t sw) {
  return (uint64_t)((addr & 0x3FFFF) >> 4) | ((uint64_t)(lbo >> 4) << 16) | ((uint64_t)(sbo >> 4) << 32) | ((uint64_t)sw << 62);
}
#define WG_FENCE() asm volatile("wgmma.fence.sync.aligned;" ::: "memory")
#define WG_COMMIT() asm volatile("wgmma.commit_group.sync.aligned;" ::: "memory")
#define WG_WAIT(n) asm volatile("wgmma.wait_group.sync.aligned " #n ";" ::: "memory")
template <int N> __device__ __forceinline__ void reg_fence(float (&d)[N]) {
#pragma unroll
  for (int i = 0; i < N; i++) asm volatile("" : "+f"(d[i])::"memory");
}
constexpr uint32_t ONES = 0x3F803F80u;

__device__ __forceinline__ void wgmma_rs64(float (&d)[32], uint32_t a0, uint32_t a1, uint32_t a2, uint32_t a3, uint64_t db, int sd) {
  asm volatile("{\n.reg .pred p;\nsetp.ne.b32 p, %37, 0;\n"
    "wgmma.mma_async.sync.aligned.m64n64k16.f32.bf16.bf16 "
    "{%0, %1, %2, %3, %4, %5, %6, %7, %8, %9, %10, %11, %12, %13, %14, %15, %16, %17, %18, %19, %20, %21, %22, %23, %24, %25, %26, %27, %28, %29, %30, %31}, "
    "{%32,%33,%34,%35}, %36, p, 1, 1, 1;\n}\n"
    : "+f"(d[0]), "+f"(d[1]), "+f"(d[2]), "+f"(d[3]), "+f"(d[4]), "+f"(d[5]), "+f"(d[6]), "+f"(d[7]),
      "+f"(d[8]), "+f"(d[9]), "+f"(d[10]), "+f"(d[11]), "+f"(d[12]), "+f"(d[13]), "+f"(d[14]), "+f"(d[15]),
      "+f"(d[16]), "+f"(d[17]), "+f"(d[18]), "+f"(d[19]), "+f"(d[20]), "+f"(d[21]), "+f"(d[22]), "+f"(d[23]),
      "+f"(d[24]), "+f"(d[25]), "+f"(d[26]), "+f"(d[27]), "+f"(d[28]), "+f"(d[29]), "+f"(d[30]), "+f"(d[31])
    : "r"(a0), "r"(a1), "r"(a2), "r"(a3), "l"(db), "r"(sd));
}

__device__ __forceinline__ void wgmma_rs192(float (&d)[96], uint32_t a0, uint32_t a1, uint32_t a2, uint32_t a3, uint64_t db, int sd) {
  asm volatile("{\n.reg .pred p;\nsetp.ne.b32 p, %101, 0;\n"
    "wgmma.mma_async.sync.aligned.m64n192k16.f32.bf16.bf16 "
    "{%0, %1, %2, %3, %4, %5, %6, %7, %8, %9, %10, %11, %12, %13, %14, %15, %16, %17, %18, %19, %20, %21, %22, %23, %24, %25, %26, %27, %28, %29, %30, %31, %32, %33, %34, %35, %36, %37, %38, %39, %40, %41, %42, %43, %44, %45, %46, %47, %48, %49, %50, %51, %52, %53, %54, %55, %56, %57, %58, %59, %60, %61, %62, %63, %64, %65, %66, %67, %68, %69, %70, %71, %72, %73, %74, %75, %76, %77, %78, %79, %80, %81, %82, %83, %84, %85, %86, %87, %88, %89, %90, %91, %92, %93, %94, %95}, "
    "{%96,%97,%98,%99}, %100, p, 1, 1, 1;\n}\n"
    : "+f"(d[0]), "+f"(d[1]), "+f"(d[2]), "+f"(d[3]), "+f"(d[4]), "+f"(d[5]), "+f"(d[6]), "+f"(d[7]),
      "+f"(d[8]), "+f"(d[9]), "+f"(d[10]), "+f"(d[11]), "+f"(d[12]), "+f"(d[13]), "+f"(d[14]), "+f"(d[15]),
      "+f"(d[16]), "+f"(d[17]), "+f"(d[18]), "+f"(d[19]), "+f"(d[20]), "+f"(d[21]), "+f"(d[22]), "+f"(d[23]),
      "+f"(d[24]), "+f"(d[25]), "+f"(d[26]), "+f"(d[27]), "+f"(d[28]), "+f"(d[29]), "+f"(d[30]), "+f"(d[31]),
      "+f"(d[32]), "+f"(d[33]), "+f"(d[34]), "+f"(d[35]), "+f"(d[36]), "+f"(d[37]), "+f"(d[38]), "+f"(d[39]),
      "+f"(d[40]), "+f"(d[41]), "+f"(d[42]), "+f"(d[43]), "+f"(d[44]), "+f"(d[45]), "+f"(d[46]), "+f"(d[47]),
      "+f"(d[48]), "+f"(d[49]), "+f"(d[50]), "+f"(d[51]), "+f"(d[52]), "+f"(d[53]), "+f"(d[54]), "+f"(d[55]),
      "+f"(d[56]), "+f"(d[57]), "+f"(d[58]), "+f"(d[59]), "+f"(d[60]), "+f"(d[61]), "+f"(d[62]), "+f"(d[63]),
      "+f"(d[64]), "+f"(d[65]), "+f"(d[66]), "+f"(d[67]), "+f"(d[68]), "+f"(d[69]), "+f"(d[70]), "+f"(d[71]),
      "+f"(d[72]), "+f"(d[73]), "+f"(d[74]), "+f"(d[75]), "+f"(d[76]), "+f"(d[77]), "+f"(d[78]), "+f"(d[79]),
      "+f"(d[80]), "+f"(d[81]), "+f"(d[82]), "+f"(d[83]), "+f"(d[84]), "+f"(d[85]), "+f"(d[86]), "+f"(d[87]),
      "+f"(d[88]), "+f"(d[89]), "+f"(d[90]), "+f"(d[91]), "+f"(d[92]), "+f"(d[93]), "+f"(d[94]), "+f"(d[95])
    : "r"(a0), "r"(a1), "r"(a2), "r"(a3), "l"(db), "r"(sd));
}

__device__ __forceinline__ void wgmma_rs32(float (&d)[16], uint32_t a0, uint32_t a1, uint32_t a2, uint32_t a3, uint64_t db, int sd) {
  asm volatile("{\n.reg .pred p;\nsetp.ne.b32 p, %21, 0;\n"
    "wgmma.mma_async.sync.aligned.m64n32k16.f32.bf16.bf16 "
    "{%0, %1, %2, %3, %4, %5, %6, %7, %8, %9, %10, %11, %12, %13, %14, %15}, "
    "{%16,%17,%18,%19}, %20, p, 1, 1, 1;\n}\n"
    : "+f"(d[0]), "+f"(d[1]), "+f"(d[2]), "+f"(d[3]), "+f"(d[4]), "+f"(d[5]), "+f"(d[6]), "+f"(d[7]),
      "+f"(d[8]), "+f"(d[9]), "+f"(d[10]), "+f"(d[11]), "+f"(d[12]), "+f"(d[13]), "+f"(d[14]), "+f"(d[15])
    : "r"(a0), "r"(a1), "r"(a2), "r"(a3), "l"(db), "r"(sd));
}

struct RowStats { float s[4], g0[4], g1[4]; };
__device__ __forceinline__ void stats_acc(RowStats& r, uint32_t a0, uint32_t a1, uint32_t a2, uint32_t a3) {
  mma16816(r.s, a0, a1, a2, a3, ONES, ONES);
  mma16816(r.g0, a0, a1, a2, a3, a0, a2);
  mma16816(r.g1, a0, a1, a2, a3, a1, a3);
}
__device__ __forceinline__ void stats_fin(const RowStats& r, int lane, float& s0, float& q0, float& s1, float& q1) {
  int g = lane >> 2, src = (lane & ~3) | (g >> 1);
  s0 = r.s[0]; s1 = r.s[2];
  q0 = __shfl_sync(~0u, (g & 1) ? r.g0[1] : r.g0[0], src);
  q1 = __shfl_sync(~0u, (g & 1) ? r.g1[3] : r.g1[2], src);
}
__device__ __forceinline__ void ln_coef(float s, float q, uint32_t& mul, uint32_t& add) {
  float mu = s * (1.f / D_);
  float var = fmaxf(q * (1.f / D_) - mu * mu, 0.f);
  float rs = rsqrtf(var + 1e-5f);
  mul = pack_bf16(rs, rs);
  float t = -mu * bf_lo(mul);
  add = pack_bf16(t, t);
}
__device__ __forceinline__ void mod_acc(float (&acc)[8], uint4 w, float cv) {
  float s = cv / (1.f + __expf(-cv));
  s = bf_lo(pack_bf16(s, s));
  acc[0] += s * bf_lo(w.x); acc[1] += s * bf_hi(w.x); acc[2] += s * bf_lo(w.y); acc[3] += s * bf_hi(w.y);
  acc[4] += s * bf_lo(w.z); acc[5] += s * bf_hi(w.z); acc[6] += s * bf_lo(w.w); acc[7] += s * bf_hi(w.w);
}
__device__ __forceinline__ float mod_reduce(float (&a)[8], int lane) {
  bool h = lane & 16;
#pragma unroll
  for (int i = 0; i < 4; i++) a[i] = (h ? a[i + 4] : a[i]) + __shfl_xor_sync(~0u, h ? a[i] : a[i + 4], 16);
  h = lane & 8;
#pragma unroll
  for (int i = 0; i < 2; i++) a[i] = (h ? a[i + 2] : a[i]) + __shfl_xor_sync(~0u, h ? a[i] : a[i + 2], 8);
  h = lane & 4;
  float v = (h ? a[1] : a[0]) + __shfl_xor_sync(~0u, h ? a[0] : a[1], 4);
  v += __shfl_xor_sync(~0u, v, 2);
  v += __shfl_xor_sync(~0u, v, 1);
  return v;
}
__device__ __forceinline__ void tab_store(uint32_t tab, int col, bool is_scale, uint4 u) {
  float a = bf_hi(u.x), b = bf_hi(u.y), c = bf_hi(u.z), d = bf_hi(u.w);
  if (is_scale) { a += 1.f; b += 1.f; c += 1.f; d += 1.f; }
  uint32_t base = tab + (col >> 4) * 64 + ((col & 7) >> 1) * 16 + ((col >> 3) & 1) * 4 + (is_scale ? 0 : 8);
  sts1(base, pack_bf16(a, b));
  sts1(base + 16, pack_bf16(c, d));
}

struct Params {
  const __nv_bfloat16 *x, *wo, *w1, *w2, *c, *wmod;
  __nv_bfloat16* out;
};

__global__ void __launch_bounds__(384, 1)
fused_block_kernel(const __grid_constant__ CUtensorMap tm_x, const __grid_constant__ CUtensorMap tm_wqkv,
                   const __grid_constant__ CUtensorMap tm_wo, const __grid_constant__ CUtensorMap tm_w1a,
                   const __grid_constant__ CUtensorMap tm_w1b, const __grid_constant__ CUtensorMap tm_w2, const Params p) {
  extern __shared__ __align__(1024) uint8_t smem_raw[];
  const uint32_t sm = (uint32_t)__cvta_generic_to_shared(smem_raw);
  const int tid = threadIdx.x, lane = tid & 31, warp = __shfl_sync(~0u, tid >> 5, 0);
  const int b = blockIdx.x;
  const int bi = b >> 3, bj = b & 7;
  auto bar = [&](int i) { return sm + SM_BAR + 8 * i; };
  TS(0);
  const uint32_t tag = ld_rlx(&g_epoch) + 1;

  if (tid == 256) {
    if (sm & 1023) __trap();
    for (int i = 0; i < B_COUNT; i++) {
      int n = 1;
      if (i == B_XFREE || (i >= B_EW && i < B_EW + 3) || i == B_ATT || i == B_EWO || (i >= B_ES && i < B_ES + 8)) n = 8;
      if (i == B_KVA || i == B_KVB) n = 4;
      mbar_init(bar(i), n);
    }
    asm volatile("fence.mbarrier_init.release.cluster;" ::: "memory");
    asm volatile("fence.proxy.async.shared::cta;" ::: "memory");
    for (int c = 0; c < 8; c++) { mbar_expect(bar(B_FX + c), 16 * KB); tma2d(sm + x_off(c), &tm_x, c * 64, bi * 128, bar(B_FX + c)); }
    mbar_expect(bar(B_FW + 0), 32 * KB); tma2d(sm + SM_WK0, &tm_wqkv, 512 + bj * 64, 0, bar(B_FW + 0));
    mbar_expect(bar(B_FW + 1), 32 * KB); tma2d(sm + SM_WK1, &tm_wqkv, 512 + bj * 64, 256, bar(B_FW + 1));
    mbar_expect(bar(B_FW + 2), 32 * KB); tma2d(sm + SM_WV, &tm_wqkv, 1024 + bj * 64, 0, bar(B_FW + 2));
  }
  uint4 mw0, mw1; float mc0 = 0.f, mc1 = 0.f;
  if (tid < 256) {
    mw0 = ld_nc4(p.wmod + (size_t)tid * (6 * D_) + b * 8);
    mw1 = ld_nc4(p.wmod + (size_t)(tid + 256) * (6 * D_) + b * 8);
    mc0 = __bfloat162float(p.c[tid]); mc1 = __bfloat162float(p.c[tid + 256]);
  }
  __syncthreads();

  if (warp >= 8) {
    asm volatile("setmaxnreg.dec.sync.aligned.u32 40;");
    asm volatile("{.reg .pred p; setp.eq.u32 p, %0, 0; @p trap; bar.arrive 1, 384;}" ::"r"(tag) : "memory");
    if (warp == 8) {
      auto load_w1 = [&](int c) {
        mbar_expect(bar(B_FS + c), SLOT);
        int cb = bj * 224;
        tma3d(sm + c * SLOT, &tm_w1a, 0, c * 64, (cb + ((bj & 1) ? 32 : 0)) >> 6, bar(B_FS + c));
        tma2d(sm + c * SLOT + 24 * KB, &tm_w1b, cb + ((bj & 1) ? 0 : 192), c * 64, bar(B_FS + c));
      };
      auto load_nb = [&](int kv, uint32_t dst, int fb) {
        int nb = bi - 2 + ((lane >> 3) & 1);
        if (bi > 0) warp_wait_flags(&g_fkv[kv][nb < 0 ? 0 : nb][bj][lane & 7], tag);
        for (int n = 0; n < 2; n++)
          if (bi - 2 + n < 0)
            for (int o = lane * 16; o < 16 * (int)KB; o += 512) sts4(dst + n * 16 * KB + o, 0, 0, 0, 0);
        __syncwarp();
        if (lane == 0) {
          asm volatile("fence.proxy.async;" ::: "memory");
          mbar_expect(bar(fb), (bi >= 2 ? 32 : 16 * bi) * KB);
          for (int n = 0; n < 2; n++)
            if (bi - 2 + n >= 0) bulk_ld(dst + n * 16 * KB, g_kv[kv][bi - 2 + n][bj], 16 * KB, bar(fb));
        }
      };
      mbar_wait(bar(B_XFREE), 0);
      if (lane == 0) {
        mbar_expect(bar(B_FW + 3), 32 * KB); tma2d(sm + SM_WV + 32 * KB, &tm_wqkv, 1024 + bj * 64, 256, bar(B_FW + 3));
        mbar_expect(bar(B_FW + 4), 32 * KB); tma2d(sm + SM_WQ, &tm_wqkv, bj * 64, 0, bar(B_FW + 4));
        mbar_expect(bar(B_FW + 5), 32 * KB); tma2d(sm + SM_WQ + 32 * KB, &tm_wqkv, bj * 64, 256, bar(B_FW + 5));
      }
      mbar_wait(bar(B_EW + 0), 0);
      if (lane == 0) {
        l2_prefetch(p.wo + (size_t)b * 2048, 4096);
        l2_prefetch(p.w1 + (size_t)b * 7168, 14336);
        l2_prefetch(p.w2 + (size_t)b * 7168, 14336);
      }
      load_nb(0, sm + SM_K, B_FKN);
      mbar_wait(bar(B_EW + 1), 0);
      load_nb(1, sm + SM_V, B_FVN);
      if (lane == 0) {
        load_w1(0); load_w1(1);
        mbar_wait(bar(B_EW + 2), 0);
        mbar_expect(bar(B_FWO + 0), 32 * KB); tma2d(sm + SM_WQ, &tm_wo, bj * 64, 0, bar(B_FWO + 0));
        mbar_expect(bar(B_FWO + 1), 32 * KB); tma2d(sm + SM_WQ + 32 * KB, &tm_wo, bj * 64, 256, bar(B_FWO + 1));
        mbar_wait(bar(B_ATT), 0);
        load_w1(2); load_w1(3); load_w1(4);
        mbar_wait(bar(B_EWO), 0);
        load_w1(5); load_w1(6); load_w1(7);
        for (int c = 0; c < 8; c++) {
          mbar_wait(bar(B_ES + c), 0);
          mbar_expect(bar(B_FS + c), SLOT);
          tma2d(sm + c * SLOT, &tm_w2, c * 64, bj * 224, bar(B_FS + c));
        }
      }
    } else if (warp < 11) {
      mbar_wait(bar(B_FX + 7), 0);
      const int col = 1024 + b * 16 + (warp - 9) * 8;
      float acc[8] = {};
#pragma unroll 1
      for (int m = 0; m < 16; m += 4) {
        uint4 w[4]; float cv[4];
#pragma unroll
        for (int u = 0; u < 4; u++) { int r = lane + 32 * (m + u); w[u] = ld_nc4(p.wmod + (size_t)r * (6 * D_) + col); cv[u] = __bfloat162float(p.c[r]); }
#pragma unroll
        for (int u = 0; u < 4; u++) mod_acc(acc, w[u], cv[u]);
      }
      float v = mod_reduce(acc, lane);
      if ((lane & 3) == 0) st_rlx(&g_mod[col + (lane >> 2)], (pack_bf16(0.f, v) & 0xffff0000u) | (tag & 0xffffu));
    } else {
      mbar_wait(bar(B_EW + 0), 0);
#pragma unroll 1
      for (int m = 0; m < 8; m++) {
        int i4 = (m * 32 + lane) * 4;
        tab_store(sm + SM_TAB, i4 & 511, i4 >= 512, wait_mod4(&g_mod[3 * D_ + i4], tag));
      }
#pragma unroll 1
      for (int m = 0; m < 8; m++) wait_mod4(&g_mod[(m < 4 ? 2 : 5) * D_ + ((m & 3) * 32 + lane) * 4], tag);
      asm volatile("fence.acq_rel.gpu;" ::: "memory");
      warp_arrive(bar(B_TAB2));
    }
  } else {
    asm volatile("setmaxnreg.inc.sync.aligned.u32 232;");
    const int wg = warp >> 2, g = lane >> 2, q = lane & 3;
    {
      float acc[8] = {};
      mod_acc(acc, mw0, mc0); mod_acc(acc, mw1, mc1);
      float v = mod_reduce(acc, lane);
      if (q == 0) sts1(sm + SM_RED + (warp * 8 + g) * 4, __float_as_uint(v));
      asm volatile("{.reg .pred p; setp.eq.u32 p, %0, 0; @p trap; bar.sync 1, 384;}" ::"r"(tag) : "memory");
      if (tid < 8) {
        const float* red = reinterpret_cast<const float*>(smem_raw + SM_RED);
        float t = 0.f;
#pragma unroll
        for (int w = 0; w < 8; w++) t += red[w * 8 + tid];
        st_rlx(&g_mod[b * 8 + tid], (pack_bf16(0.f, t) & 0xffff0000u) | (tag & 0xffffu));
      }
    }
    TS(1);
    uint32_t qf[16];
    {
      uint32_t a[128];
      RowStats rs = {};
      const int lrow = warp * 16 + (lane & 15);
#pragma unroll
      for (int c = 0; c < 8; c++) {
        mbar_wait(bar(B_FX + c), 0);
#pragma unroll
        for (int k = 0; k < 4; k++) {
          uint32_t ad = sm + x_off(c) + lrow * 128 + (((2 * k + (lane >> 4)) ^ (lane & 7)) << 4);
          int i = (c * 4 + k) * 4;
          asm volatile("ldmatrix.sync.aligned.m8n8.x4.shared.b16 {%0,%1,%2,%3}, [%4];" : "=r"(a[i]), "=r"(a[i + 1]), "=r"(a[i + 2]), "=r"(a[i + 3]) : "r"(ad) : "memory");
          stats_acc(rs, a[i], a[i + 1], a[i + 2], a[i + 3]);
        }
      }
      warp_arrive(bar(B_XFREE));
      TS(2);
      float s0, q0, s1, q1; uint32_t m0, d0, m1, d1;
      stats_fin(rs, lane, s0, q0, s1, q1);
      ln_coef(s0, q0, m0, d0); ln_coef(s1, q1, m1, d1);
#pragma unroll
      for (int i = 0; i < 128; i += 2) { a[i] = hfma2(a[i], m0, d0); a[i + 1] = hfma2(a[i + 1], m1, d1); }
      tab_store(sm + SM_TAB, (tid * 4) & 511, tid >= 128, wait_mod4(&g_mod[tid * 4], tag));
      asm volatile("bar.sync 2, 256;" ::: "memory");
      TS(3);
#pragma unroll
      for (int k = 0; k < 32; k++) {
        uint4 t = lds4(sm + SM_TAB + k * 64 + q * 16);
        a[4 * k] = hfma2(a[4 * k], t.x, t.z); a[4 * k + 1] = hfma2(a[4 * k + 1], t.x, t.z);
        a[4 * k + 2] = hfma2(a[4 * k + 2], t.y, t.w); a[4 * k + 3] = hfma2(a[4 * k + 3], t.y, t.w);
      }
      TS(4);
#pragma unroll 1
      for (int ch = 0; ch < 3; ch++) {
        float acc[32];
        const uint32_t w0 = sm + (ch == 0 ? SM_WK0 : (ch == 1 ? SM_WV : SM_WQ));
        const uint32_t w1 = sm + (ch == 0 ? SM_WK1 : (ch == 1 ? SM_WV + 32 * KB : SM_WQ + 32 * KB));
        if (wg == 1 || ch > 0) asm volatile("bar.sync %0, 256;" ::"r"(3 + wg) : "memory");
        mbar_wait(bar(B_FW + 2 * ch), 0);
        WG_FENCE();
#pragma unroll
        for (int k = 0; k < 16; k++) wgmma_rs64(acc, a[4 * k], a[4 * k + 1], a[4 * k + 2], a[4 * k + 3], desc_b(w0 + k * 2048, 0, 1024, 1), k != 0);
        mbar_wait(bar(B_FW + 2 * ch + 1), 0);
        WG_FENCE();
#pragma unroll
        for (int k = 16; k < 32; k++) wgmma_rs64(acc, a[4 * k], a[4 * k + 1], a[4 * k + 2], a[4 * k + 3], desc_b(w1 + (k - 16) * 2048, 0, 1024, 1), 1);
        WG_COMMIT();
        if (wg == 0 || ch < 2) asm volatile("bar.arrive %0, 256;" ::"r"(4 - wg) : "memory");
        WG_WAIT(0);
        reg_fence(acc);
        warp_arrive(bar(B_EW + ch));
#pragma unroll
        for (int h = 0; h < 4; h++) {
          qf[4 * h] = pack_bf16(acc[8 * h], acc[8 * h + 1]); qf[4 * h + 1] = pack_bf16(acc[8 * h + 2], acc[8 * h + 3]);
          qf[4 * h + 2] = pack_bf16(acc[8 * h + 4], acc[8 * h + 5]); qf[4 * h + 3] = pack_bf16(acc[8 * h + 6], acc[8 * h + 7]);
        }
        if (ch < 2) {
          const uint32_t dst = sm + (ch == 0 ? SM_K : SM_V) + 32 * KB + warp * 2048 + lane * 16;
          uint4* gdst = &g_kv[ch][bi][bj][warp * 128 + lane];
#pragma unroll
          for (int h = 0; h < 4; h++) {
            uint32_t r0 = qf[4 * h], r1 = qf[4 * h + 2], r2 = qf[4 * h + 1], r3 = qf[4 * h + 3];
            if (ch == 1) { r0 = movm(qf[4 * h]); r1 = movm(qf[4 * h + 1]); r2 = movm(qf[4 * h + 2]); r3 = movm(qf[4 * h + 3]); }
            stg4(gdst + h * 32, r0, r1, r2, r3);
            sts4(dst + h * 512, r0, r1, r2, r3);
          }
          if (ch == 1) warp_arrive(bar(B_KVA + wg));
          warp_publish(&g_fkv[ch][bi][bj][warp], tag);
        }
        TS(5 + ch);
      }
    }
    {
      mbar_wait(bar(B_KVA), 0);
      if (wg == 1) mbar_wait(bar(B_KVB), 0);
      mbar_wait(bar(B_FKN), 0);
      TS(8);
      const float sc = 0.25f * 1.4426950408889634f;
      const int tmin = 16 - 8 * bi - warp;
      const bool v00 = 2 * q <= g, v01 = 2 * q + 1 <= g;
#pragma unroll 1
      for (int h = 0; h < 4; h++) {
        const uint32_t kb = sm + SM_K + warp * 2048 + h * 512 + lane * 16;
        float s[17][2][4];
#pragma unroll
        for (int t = 0; t < 17; t++) {
          uint4 kf = lds4(kb + t * 2048);
          float init = (t < 16 && t < tmin) ? -INFINITY : 0.f;
#pragma unroll
          for (int e = 0; e < 4; e++) { s[t][0][e] = init; s[t][1][e] = init; }
          mma16816(s[t][0], qf[0], qf[1], qf[2], qf[3], kf.x, kf.y);
          mma16816(s[t][1], qf[0], qf[1], qf[2], qf[3], kf.z, kf.w);
        }
        s[0][0][0] = v00 ? s[16][0][0] : s[0][0][0]; s[0][0][1] = v01 ? s[16][0][1] : s[0][0][1];
        s[0][0][2] = s[16][0][2]; s[0][0][3] = s[16][0][3];
        s[0][1][2] = v00 ? s[16][1][2] : s[0][1][2]; s[0][1][3] = v01 ? s[16][1][3] : s[0][1][3];
        float mx0 = -INFINITY, mx1 = -INFINITY, my0 = -INFINITY, my1 = -INFINITY;
#pragma unroll
        for (int t = 0; t < 16; t++) {
          mx0 = fmaxf(mx0, fmaxf(s[t][0][0], s[t][0][1])); my0 = fmaxf(my0, fmaxf(s[t][1][0], s[t][1][1]));
          mx1 = fmaxf(mx1, fmaxf(s[t][0][2], s[t][0][3])); my1 = fmaxf(my1, fmaxf(s[t][1][2], s[t][1][3]));
        }
        mx0 = fmaxf(mx0, my0); mx1 = fmaxf(mx1, my1);
        mx0 = fmaxf(mx0, __shfl_xor_sync(~0u, mx0, 1)); mx1 = fmaxf(mx1, __shfl_xor_sync(~0u, mx1, 1));
        mx0 = fmaxf(mx0, __shfl_xor_sync(~0u, mx0, 2)); mx1 = fmaxf(mx1, __shfl_xor_sync(~0u, mx1, 2));
        const float b0 = -mx0 * sc, b1 = -mx1 * sc;
        if (h == 0) mbar_wait(bar(B_FVN), 0);
        const uint32_t vb = kb + (SM_V - SM_K);
        float o0[4] = {}, o1[4] = {}, l[4] = {};
#pragma unroll
        for (int t = 0; t < 16; t++) {
          uint4 vf = lds4(vb + t * 2048);
          uint32_t p0 = pack_bf16(ex2(fmaf(s[t][0][0], sc, b0)), ex2(fmaf(s[t][0][1], sc, b0)));
          uint32_t p1 = pack_bf16(ex2(fmaf(s[t][0][2], sc, b1)), ex2(fmaf(s[t][0][3], sc, b1)));
          uint32_t p2 = pack_bf16(ex2(fmaf(s[t][1][0], sc, b0)), ex2(fmaf(s[t][1][1], sc, b0)));
          uint32_t p3 = pack_bf16(ex2(fmaf(s[t][1][2], sc, b1)), ex2(fmaf(s[t][1][3], sc, b1)));
          mma16816(l, p0, p1, p2, p3, ONES, ONES);
          if (t == 0) {
            const uint32_t mk = (v00 ? 0xffffu : 0u) | (v01 ? 0xffff0000u : 0u);
            uint4 vd = lds4(vb + 16 * 2048);
            mma16816(o0, p0 & mk, p1, 0u, p3 & mk, vd.x, vd.y);
            mma16816(o1, p0 & mk, p1, 0u, p3 & mk, vd.z, vd.w);
            p0 &= ~mk; p1 = 0u; p3 &= ~mk;
          }
          mma16816(o0, p0, p1, p2, p3, vf.x, vf.y);
          mma16816(o1, p0, p1, p2, p3, vf.z, vf.w);
        }
        const float r0 = __fdividef(1.f, l[0]), r1 = __fdividef(1.f, l[2]);
        stg4(&g_o[bi][warp][bj * 4 + h][lane], pack_bf16(o0[0] * r0, o0[1] * r0), pack_bf16(o0[2] * r1, o0[3] * r1),
             pack_bf16(o1[0] * r0, o1[1] * r0), pack_bf16(o1[2] * r1, o1[3] * r1));
        if (h >= 2) warp_publish(&g_fo[bi][warp][h][bj], tag);
#pragma unroll
        for (int i = 0; i < 12; i++) qf[i] = qf[i + 4];
        TS(9 + h);
      }
      asm volatile("fence.proxy.async.shared::cta;" ::: "memory");
      warp_arrive(bar(B_ATT));
    }
    {
      uint4 a[32];
      warp_wait_flags(&g_fo[bi][warp][2][lane & 7], tag);
#pragma unroll
      for (int k = 0; k < 32; k++) if ((k & 3) != 3) a[k] = ld_rlx4(&g_o[bi][warp][k][lane]);
      uint32_t xr[16]; uint2 ga[8];
      const __nv_bfloat16* xp = p.x + (size_t)(bi * 128 + warp * 16 + g) * D_ + bj * 64 + 2 * q;
#pragma unroll
      for (int n = 0; n < 8; n++) {
        xr[2 * n] = __ldg(reinterpret_cast<const uint32_t*>(xp + n * 8));
        xr[2 * n + 1] = __ldg(reinterpret_cast<const uint32_t*>(xp + 8 * D_ + n * 8));
      }
      mbar_wait(bar(B_TAB2), 0);
      warp_wait_flags(&g_fo[bi][warp][3][lane & 7], tag);
#pragma unroll
      for (int k = 3; k < 32; k += 4) a[k] = ld_rlx4(&g_o[bi][warp][k][lane]);
      TS(13);
      float acc[32];
      mbar_wait(bar(B_FWO), 0); mbar_wait(bar(B_FWO + 1), 0);
      WG_FENCE();
#pragma unroll
      for (int k = 0; k < 32; k++) if ((k & 3) != 3) wgmma_rs64(acc, a[k].x, a[k].y, a[k].z, a[k].w, desc_b(sm + SM_WQ + k * 2048, 0, 1024, 1), k != 0);
      WG_FENCE();
#pragma unroll
      for (int k = 3; k < 32; k += 4) wgmma_rs64(acc, a[k].x, a[k].y, a[k].z, a[k].w, desc_b(sm + SM_WQ + k * 2048, 0, 1024, 1), 1);
      WG_COMMIT();
#pragma unroll
      for (int n = 0; n < 8; n++) {
        ga[n] = ld_rlx2(&g_mod[2 * D_ + bj * 64 + n * 8 + 2 * q]);
      }
      WG_WAIT(0);
      reg_fence(acc);
      warp_arrive(bar(B_EWO));
      TS(14);
      RowStats rs = {};
#pragma unroll
      for (int k = 0; k < 4; k++) {
        uint32_t r[4];
#pragma unroll
        for (int e = 0; e < 4; e++) {
          int n = 2 * k + (e >> 1), i = 4 * n + 2 * (e & 1);
          uint32_t xv = xr[2 * n + (e & 1)];
          r[e] = pack_bf16(fmaf(bf_hi(ga[n].x), acc[i], bf_lo(xv)), fmaf(bf_hi(ga[n].y), acc[i + 1], bf_hi(xv)));
        }
        stg4(&g_x1[bi][warp][bj * 4 + k][lane], r[0], r[1], r[2], r[3]);
        stats_acc(rs, r[0], r[1], r[2], r[3]);
      }
      float s0, q0, s1, q1;
      stats_fin(rs, lane, s0, q0, s1, q1);
      if (q < 2) g_st[bi][warp][g + 8 * q][bj] = q ? make_float2(s1, q1) : make_float2(s0, q0);
      warp_publish(&g_fx[bi][warp][bj], tag);
      TS(15);
    }
    uint32_t hid[56];
    {
      warp_wait_flags(&g_fx[bi][warp][lane & 7], tag);
      TS(16);
      const uint4* xa = &g_x1[bi][warp][0][lane];
      uint4 st0 = ld_rlx4(&g_st[bi][warp][g][2 * q]), st1 = ld_rlx4(&g_st[bi][warp][g + 8][2 * q]);
      uint4 raw[2][4];
#pragma unroll
      for (int u = 0; u < 8; u++) raw[u >> 2][u & 3] = ld_rlx4(xa + u * 32);
      float s0 = __uint_as_float(st0.x) + __uint_as_float(st0.z), q0 = __uint_as_float(st0.y) + __uint_as_float(st0.w);
      float s1 = __uint_as_float(st1.x) + __uint_as_float(st1.z), q1 = __uint_as_float(st1.y) + __uint_as_float(st1.w);
#pragma unroll
      for (int o = 1; o < 4; o <<= 1) {
        s0 += __shfl_xor_sync(~0u, s0, o); q0 += __shfl_xor_sync(~0u, q0, o);
        s1 += __shfl_xor_sync(~0u, s1, o); q1 += __shfl_xor_sync(~0u, q1, o);
      }
      uint32_t m0, d0, m1, d1;
      ln_coef(s0, q0, m0, d0); ln_coef(s1, q1, m1, d1);
      float accA[96], accB[16];
      uint32_t an[2][16];
#pragma unroll 1
      for (int c2 = 0; c2 < 8; c2 += 2) {
#pragma unroll
        for (int u = 0; u < 2; u++) {
          const int c = c2 + u;
#pragma unroll
          for (int k = 0; k < 4; k++) {
            uint4 t = lds4(sm + SM_TAB + (c * 4 + k) * 64 + q * 16);
            an[u][4 * k] = hfma2(hfma2(raw[u][k].x, m0, d0), t.x, t.z); an[u][4 * k + 1] = hfma2(hfma2(raw[u][k].y, m1, d1), t.x, t.z);
            an[u][4 * k + 2] = hfma2(hfma2(raw[u][k].z, m0, d0), t.y, t.w); an[u][4 * k + 3] = hfma2(hfma2(raw[u][k].w, m1, d1), t.y, t.w);
          }
          if (c2 < 6) {
#pragma unroll
            for (int k = 0; k < 4; k++) raw[u][k] = ld_rlx4(xa + ((c + 2) * 4 + k) * 32);
          }
          mbar_wait(bar(B_FS + c), 0);
          WG_FENCE();
#pragma unroll
          for (int k = 0; k < 4; k++) {
            wgmma_rs192(accA, an[u][4 * k], an[u][4 * k + 1], an[u][4 * k + 2], an[u][4 * k + 3], desc_b(sm + c * SLOT + k * 2048, 8 * KB, 1024, 1), (c | k) != 0);
            wgmma_rs32(accB, an[u][4 * k], an[u][4 * k + 1], an[u][4 * k + 2], an[u][4 * k + 3], desc_b(sm + c * SLOT + 24 * KB + k * 1024, 0, 512, 2), (c | k) != 0);
          }
          WG_COMMIT();
          WG_WAIT(1);
          if (c > 0) warp_arrive(bar(B_ES + c - 1));
        }
      }
      WG_WAIT(0);
      reg_fence(accA); reg_fence(accB);
      warp_arrive(bar(B_ES + 7));
#pragma unroll
      for (int i = 0; i < 48; i++) hid[i] = pack_relu(accA[2 * i], accA[2 * i + 1]);
#pragma unroll
      for (int i = 0; i < 8; i++) hid[48 + i] = pack_relu(accB[2 * i], accB[2 * i + 1]);
      TS(17);
    }
    {
      const uint32_t offA = (bj & 1) ? 32 * 128 : 0, offB = (bj & 1) ? 0 : 192 * 128;
      float acc[2][32];
      auto issue = [&](float (&d)[32], int c) {
        mbar_wait(bar(B_FS + c), 1);
        WG_FENCE();
#pragma unroll
        for (int k = 0; k < 14; k++)
          wgmma_rs64(d, hid[4 * k], hid[4 * k + 1], hid[4 * k + 2], hid[4 * k + 3],
                     desc_b(sm + c * SLOT + (k < 12 ? offA + k * 2048 : offB + (k - 12) * 2048), 0, 1024, 1), k != 0);
        WG_COMMIT();
      };
      auto store = [&](float (&d)[32], int c) {
        reg_fence(d);
#pragma unroll
        for (int k = 0; k < 4; k++)
          stg4(&g_part[bi][warp][c * 4 + k][bj][lane], pack_bf16(d[8 * k], d[8 * k + 1]), pack_bf16(d[8 * k + 2], d[8 * k + 3]),
               pack_bf16(d[8 * k + 4], d[8 * k + 5]), pack_bf16(d[8 * k + 6], d[8 * k + 7]));
      };
      auto reduce = [&](int cc) {
        const int s = cc * 8 + warp;
        uint4 xv = ld_rlx4(&g_x1[bi][bj][s][lane]);
        uint2 g0 = ld_rlx2(&g_mod[5 * D_ + s * 16 + 2 * q]), g1 = ld_rlx2(&g_mod[5 * D_ + s * 16 + 8 + 2 * q]);
        warp_wait_flags(&g_fp[bi][bj][cc][lane & 7], tag);
        uint4 v[8];
#pragma unroll
        for (int u = 0; u < 8; u++) v[u] = ld_rlx4(&g_part[bi][bj][s][u][lane]);
        float f[8] = {};
#pragma unroll
        for (int u = 0; u < 8; u++) {
          f[0] += bf_lo(v[u].x); f[1] += bf_hi(v[u].x); f[2] += bf_lo(v[u].y); f[3] += bf_hi(v[u].y);
          f[4] += bf_lo(v[u].z); f[5] += bf_hi(v[u].z); f[6] += bf_lo(v[u].w); f[7] += bf_hi(v[u].w);
        }
        uint32_t* op = reinterpret_cast<uint32_t*>(p.out + (size_t)(bi * 128 + bj * 16 + g) * D_ + s * 16 + 2 * q);
        op[0] = pack_bf16(fmaf(bf_hi(g0.x), f[0], bf_lo(xv.x)), fmaf(bf_hi(g0.y), f[1], bf_hi(xv.x)));
        op[4 * D_] = pack_bf16(fmaf(bf_hi(g0.x), f[2], bf_lo(xv.y)), fmaf(bf_hi(g0.y), f[3], bf_hi(xv.y)));
        op[4] = pack_bf16(fmaf(bf_hi(g1.x), f[4], bf_lo(xv.z)), fmaf(bf_hi(g1.y), f[5], bf_hi(xv.z)));
        op[4 * D_ + 4] = pack_bf16(fmaf(bf_hi(g1.x), f[6], bf_lo(xv.w)), fmaf(bf_hi(g1.y), f[7], bf_hi(xv.w)));
      };
      warp_wait_flags(&g_fx[bi][bj][lane & 7], tag);
      issue(acc[0], 0);
#pragma unroll
      for (int cc = 0; cc < 4; cc++) {
        issue(acc[1], 2 * cc + 1);
        WG_WAIT(1);
        store(acc[0], 2 * cc);
        if (cc < 3) {
          issue(acc[0], 2 * cc + 2);
          if (cc >= 2) reduce(cc - 2);
          WG_WAIT(1);
        } else {
          reduce(1);
          WG_WAIT(0);
        }
        store(acc[1], 2 * cc + 1);
        warp_publish(&g_fp[bi][warp][cc][bj], tag);
        TS(18 + cc);
      }
      reduce(2);
      reduce(3);
      TS(22);
      if (b == 0 && tid == 0) st_rlx(&g_epoch, tag);
    }
  }
}

typedef CUresult (*EncodeFn)(CUtensorMap*, CUtensorMapDataType, cuuint32_t, void*, const cuuint64_t*, const cuuint64_t*,
                             const cuuint32_t*, const cuuint32_t*, CUtensorMapInterleave, CUtensorMapSwizzle,
                             CUtensorMapL2promotion, CUtensorMapFloatOOBfill);

void make_map(EncodeFn enc, CUtensorMap* tm, const void* base, int rank, const cuuint64_t* dims, const cuuint64_t* strides,
              const cuuint32_t* box, CUtensorMapSwizzle sw) {
  cuuint32_t es[3] = {1, 1, 1};
  enc(tm, CU_TENSOR_MAP_DATA_TYPE_BFLOAT16, rank, const_cast<void*>(base), dims, strides, box, es,
      CU_TENSOR_MAP_INTERLEAVE_NONE, sw, CU_TENSOR_MAP_L2_PROMOTION_L2_128B, CU_TENSOR_MAP_FLOAT_OOB_FILL_NONE);
}
void make_map2(EncodeFn enc, CUtensorMap* tm, const void* base, int rows, int cols, int bc, int br, CUtensorMapSwizzle sw) {
  cuuint64_t dims[2] = {(cuuint64_t)cols, (cuuint64_t)rows}, strides[1] = {(cuuint64_t)cols * 2};
  cuuint32_t box[2] = {(cuuint32_t)bc, (cuuint32_t)br};
  make_map(enc, tm, base, 2, dims, strides, box, sw);
}

}

extern "C" void kernel_launch(void* const* d_in, const int* in_sizes, int n_in, void* d_out, int out_size) {
  EncodeFn enc = nullptr;
  cudaDriverEntryPointQueryResult qr;
  cudaGetDriverEntryPoint("cuTensorMapEncodeTiled", (void**)&enc, cudaEnableDefault, &qr);
  CUtensorMap tx, tqkv, two, tw1a, tw1b, tw2;
  make_map2(enc, &tx, d_in[0], S_, D_, 64, 128, CU_TENSOR_MAP_SWIZZLE_128B);
  make_map2(enc, &tqkv, d_in[1], D_, 3 * D_, 64, 256, CU_TENSOR_MAP_SWIZZLE_128B);
  make_map2(enc, &two, d_in[2], D_, D_, 64, 256, CU_TENSOR_MAP_SWIZZLE_128B);
  {
    cuuint64_t dims[3] = {64, (cuuint64_t)D_, DFF / 64}, strides[2] = {DFF * 2, 128};
    cuuint32_t box[3] = {64, 64, 3};
    make_map(enc, &tw1a, d_in[4], 3, dims, strides, box, CU_TENSOR_MAP_SWIZZLE_128B);
  }
  make_map2(enc, &tw1b, d_in[4], D_, DFF, 32, 64, CU_TENSOR_MAP_SWIZZLE_64B);
  make_map2(enc, &tw2, d_in[5], DFF, D_, 64, 224, CU_TENSOR_MAP_SWIZZLE_128B);
  Params p;
  p.x = (const __nv_bfloat16*)d_in[0]; p.wo = (const __nv_bfloat16*)d_in[2]; p.w1 = (const __nv_bfloat16*)d_in[4];
  p.w2 = (const __nv_bfloat16*)d_in[5]; p.c = (const __nv_bfloat16*)d_in[6]; p.wmod = (const __nv_bfloat16*)d_in[7];
  p.out = (__nv_bfloat16*)d_out;
  cudaFuncSetAttribute(fused_block_kernel, cudaFuncAttributeMaxDynamicSharedMemorySize, SM_TOTAL);
  fused_block_kernel<<<128, 384, SM_TOTAL, cudaStreamPerThread>>>(tx, tqkv, two, tw1a, tw1b, tw2, p);
}
```

```cpp
#include <cuda_runtime.h>
#include <cuda_bf16.h>
#include <cuda.h>
#include <stdint.h>

#define DEP 2
#define W1D 1
#define W2D 1
#define LAG 2
#define G1 5
#define G2 9
#define NS "40"
#define BACKOFF "nanosleep.u32 " NS ";\n"
#define SPIN 5
#define B5 1
#define A3L 1
#define MAPMODE 0
#define TS(n)
#define TSDUMP()

namespace {

constexpr int S_ = 2048, D_ = 512, DFF = 1792;
constexpr uint32_t KB = 1024;
constexpr uint32_t SM_WV = 0;
constexpr uint32_t SM_K = 64 * KB;
constexpr uint32_t SM_V = 112 * KB;
constexpr uint32_t SM_WK0 = 64 * KB, SM_WK1 = 112 * KB;
constexpr uint32_t SM_WQ = 160 * KB;
constexpr uint32_t SLOT = 28 * KB;
constexpr uint32_t SM_TAB = 224 * KB;
constexpr uint32_t SM_RED = 0;
constexpr uint32_t SM_RED2 = SM_TAB;
constexpr uint32_t SM_BAR = 226 * KB;
constexpr uint32_t SM_TOTAL = 227 * KB;
__device__ __forceinline__ uint32_t x_off(int c) {
  return c < 2 ? (32 + 16 * c) * KB : (c == 2 ? 96 * KB : (144 + 16 * (c - 3)) * KB);
}
enum { B_FX = 0  , B_XFREE = 8, B_FW = 9  , B_EW = 15  , B_FKN = 18, B_FVN = 19,
       B_KVA = 20, B_KVB = 21, B_FWO = 22, B_TAB1 = 23, B_ATT = 24, B_EWO = 25, B_FS = 26  , B_ES = 34  ,
       B_TAB2 = 42, B_KST = 43, B_OST = 44  , B_FO = 46  , B_EO = 48, B_XST = 49, B_XOK = 50, B_RED = 51, B_RED2 = 52, B_RED3 = 53, B_COUNT = 54 };
__host__ __device__ constexpr int bar_count(int i) {
  return (i == B_XFREE || (i >= B_EW && i < B_EW + 3) || i == B_ATT || i == B_EWO || (i >= B_ES && i < B_ES + 8) || i == B_KST ||
          i == B_EO || i == B_XST || i == B_RED || i == B_RED2 || i == B_TAB1) ? 8
       : (i == B_KVA || i == B_KVB || i == B_OST || i == B_OST + 1) ? 4 : (i == B_TAB2 || i == B_RED3) ? 2 : 1;
}

struct Scratch {
  uint4 kv[2][16][8][8 * 4 * 32];
  uint4 o[16][2][4][4][8][32];
  uint4 x1[16][8][32][32];
  uint32_t x1e[16][8][8][32][4];
  uint4 part[16][8][32][8][32];
  uint4 st[16][8][8][8];
  uint32_t mod1[8][4][2 * D_];
  uint32_t mod2[4][4 * D_];
  float gate[128][2 * D_];
  uint32_t epoch[128][32];
  uint32_t fkv[2][16][8][8];
  uint32_t fo[16][2][8];
  uint32_t fx[16][8];
};
__device__ Scratch g_scratch;

__device__ __forceinline__ void mbar_init(uint32_t b, int n) { asm volatile("mbarrier.init.shared.b64 [%0], %1;" ::"r"(b), "r"(n)); }
__device__ __forceinline__ void mbar_arrive(uint32_t b) { asm volatile("mbarrier.arrive.shared.b64 _, [%0];" ::"r"(b) : "memory"); }
__device__ __forceinline__ void mbar_expect(uint32_t b, uint32_t n) { asm volatile("mbarrier.arrive.expect_tx.shared.b64 _, [%0], %1;" ::"r"(b), "r"(n) : "memory"); }
__device__ __forceinline__ void mbar_wait(uint32_t b, uint32_t parity) {
  asm volatile("{\n.reg .pred p, e;\n.reg .u32 n;\nmov.u32 n, 0;\nLW:\n"
               "mbarrier.try_wait.parity.shared.b64 p, [%0], %1;\n@p bra.uni LD;\n"
               "add.u32 n, n, 1;\nsetp.gt.u32 e, n, 4194304;\n@e trap;\nbra.uni LW;\nLD:\n}" ::"r"(b), "r"(parity) : "memory");
}
__device__ __forceinline__ void warp_arrive(uint32_t b) {
  asm volatile("{\n.reg .pred p;\nbar.warp.sync 0xffffffff;\nelect.sync _|p, 0xffffffff;\n@p mbarrier.arrive.shared.b64 _, [%0];\n}" ::"r"(b) : "memory");
}
__device__ __forceinline__ void tma2d(uint32_t dst, const CUtensorMap* tm, int c0, int c1, uint32_t bar) {
  asm volatile("cp.async.bulk.tensor.2d.shared::cluster.global.mbarrier::complete_tx::bytes [%0], [%1, {%3,%4}], [%2];"
               ::"r"(dst), "l"(tm), "r"(bar), "r"(c0), "r"(c1) : "memory");
}
__device__ __forceinline__ void tma3d(uint32_t dst, const CUtensorMap* tm, int c0, int c1, int c2, uint32_t bar) {
  asm volatile("cp.async.bulk.tensor.3d.shared::cluster.global.mbarrier::complete_tx::bytes [%0], [%1, {%3,%4,%5}], [%2];"
               ::"r"(dst), "l"(tm), "r"(bar), "r"(c0), "r"(c1), "r"(c2) : "memory");
}
__device__ __forceinline__ void bulk_ld(uint32_t dst, const void* src, uint32_t bytes, uint32_t bar) {
  asm volatile("cp.async.bulk.shared::cluster.global.mbarrier::complete_tx::bytes [%0], [%1], %2, [%3];"
               ::"r"(dst), "l"(src), "r"(bytes), "r"(bar) : "memory");
}
__device__ __forceinline__ void l2_prefetch(const void* src, uint32_t bytes) {
  asm volatile("cp.async.bulk.prefetch.L2.global [%0], %1;" ::"l"(src), "r"(bytes) : "memory");
}
__device__ __forceinline__ uint32_t ld_rlx(const uint32_t* p) { uint32_t v; asm volatile("ld.relaxed.gpu.global.u32 %0, [%1];" : "=r"(v) : "l"(p) : "memory"); return v; }
__device__ __forceinline__ uint4 ld_rlx4(const void* p) { uint4 v; asm volatile("ld.relaxed.gpu.global.v4.u32 {%0,%1,%2,%3}, [%4];" : "=r"(v.x), "=r"(v.y), "=r"(v.z), "=r"(v.w) : "l"(p) : "memory"); return v; }
__device__ __forceinline__ uint4 ld_nc4(const void* p) { uint4 v; asm volatile("ld.global.nc.L1::no_allocate.v4.u32 {%0,%1,%2,%3}, [%4];" : "=r"(v.x), "=r"(v.y), "=r"(v.z), "=r"(v.w) : "l"(p)); return v; }
__device__ __forceinline__ void st_rel(uint32_t* p, uint32_t v) { asm volatile("st.release.gpu.global.u32 [%0], %1;" ::"l"(p), "r"(v) : "memory"); }
__device__ __forceinline__ void st_rlx(uint32_t* p, uint32_t v) { asm volatile("st.relaxed.gpu.global.u32 [%0], %1;" ::"l"(p), "r"(v) : "memory"); }
__device__ __forceinline__ void stg4(void* p, uint32_t a, uint32_t b, uint32_t c, uint32_t d) { asm volatile("st.global.v4.u32 [%0], {%1,%2,%3,%4};" ::"l"(p), "r"(a), "r"(b), "r"(c), "r"(d) : "memory"); }
__device__ __forceinline__ void sts4(uint32_t a_, uint32_t a, uint32_t b, uint32_t c, uint32_t d) { asm volatile("st.shared.v4.u32 [%0], {%1,%2,%3,%4};" ::"r"(a_), "r"(a), "r"(b), "r"(c), "r"(d) : "memory"); }
__device__ __forceinline__ void sts1(uint32_t a_, uint32_t a) { asm volatile("st.shared.u32 [%0], %1;" ::"r"(a_), "r"(a) : "memory"); }
__device__ __forceinline__ uint4 lds4(uint32_t a) { uint4 v; asm volatile("ld.shared.v4.u32 {%0,%1,%2,%3}, [%4];" : "=r"(v.x), "=r"(v.y), "=r"(v.z), "=r"(v.w) : "r"(a) : "memory"); return v; }
__device__ __forceinline__ void warp_wait_flags(const uint32_t* p, uint32_t tag) {
  asm volatile("{\n.reg .pred p, e;\n.reg .u32 n, v;\nmov.u32 n, 0;\nLW:\n"
               "ld.relaxed.gpu.global.u32 v, [%0];\nsetp.eq.u32 p, v, %1;\nvote.sync.all.pred p, p, 0xffffffff;\n@p bra.uni LD;\n" BACKOFF
               "add.u32 n, n, 1;\nsetp.gt.u32 e, n, 4194304;\n@e trap;\nbra.uni LW;\nLD:\nfence.acquire.gpu;\n}" ::"l"(p), "r"(tag) : "memory");
}
__device__ __forceinline__ uint32_t pack_bf16(float lo, float hi) { uint32_t r; asm("cvt.rn.bf16x2.f32 %0, %1, %2;" : "=r"(r) : "f"(hi), "f"(lo)); return r; }
__device__ __forceinline__ float round_even(float v) { return __uint_as_float((__float_as_uint(v) + 0x10000u) & 0xfffe0000u); }
__device__ __forceinline__ void spin_tag(const void* p, uint32_t par) {
  asm volatile("{\n.reg .pred p, e;\n.reg .u32 n, v;\nmov.u32 n, 0;\nLW:\n"
               "ld.relaxed.gpu.global.u32 v, [%0];\nand.b32 v, v, 1;\nsetp.eq.u32 p, v, %1;\nvote.sync.all.pred p, p, 0xffffffff;\n@p bra.uni LD;\n" BACKOFF
               "add.u32 n, n, 1;\nsetp.gt.u32 e, n, 4194304;\n@e trap;\nbra.uni LW;\nLD:\n}" ::"l"(p), "r"(par) : "memory");
}
template <int N> __device__ __forceinline__ void check_tags(uint4 (&v)[N], const uint4* p, int lane, uint32_t par) {
  while (true) {
    uint32_t bad = 0;
#pragma unroll
    for (int i = 0; i < N; i++) bad |= v[i].x ^ par;
    if (!__any_sync(~0u, bad & 1)) break;
    spin_tag(p - lane + (lane % N) * 32 + 31, par);
#pragma unroll
    for (int i = 0; i < N; i++) v[i] = ld_rlx4(p + i * 32);
  }
#pragma unroll
  for (int i = 0; i < N; i++) asm volatile("and.b32 %0, %0, -2;" : "+r"(v[i].x));
}
__device__ __forceinline__ uint32_t pack_relu(float lo, float hi) { uint32_t r; asm("cvt.rn.relu.bf16x2.f32 %0, %1, %2;" : "=r"(r) : "f"(hi), "f"(lo)); return r; }
__device__ __forceinline__ uint32_t hfma2(uint32_t a, uint32_t b, uint32_t c) { uint32_t r; asm("fma.rn.bf16x2 %0, %1, %2, %3;" : "=r"(r) : "r"(a), "r"(b), "r"(c)); return r; }
__device__ __forceinline__ void hfma2v(uint32_t& a, uint32_t b, uint32_t c) { asm volatile("fma.rn.bf16x2 %0, %0, %1, %2;" : "+r"(a) : "r"(b), "r"(c)); }
__device__ __forceinline__ float bf_lo(uint32_t v) { return __uint_as_float(v << 16); }
__device__ __forceinline__ float bf_hi(uint32_t v) { return __uint_as_float(v & 0xffff0000u); }
__device__ __forceinline__ float ex2(float x) { float r; asm("ex2.approx.ftz.f32 %0, %1;" : "=f"(r) : "f"(x)); return r; }
__device__ __forceinline__ uint32_t movm(uint32_t a) { uint32_t r; asm volatile("movmatrix.sync.aligned.m8n8.trans.b16 %0, %1;" : "=r"(r) : "r"(a)); return r; }
__device__ __forceinline__ void mma16816(float (&c)[4], uint32_t a0, uint32_t a1, uint32_t a2, uint32_t a3, uint32_t b0, uint32_t b1) {
  asm("mma.sync.aligned.m16n8k16.row.col.f32.bf16.bf16.f32 {%0,%1,%2,%3}, {%4,%5,%6,%7}, {%8,%9}, {%0,%1,%2,%3};"
      : "+f"(c[0]), "+f"(c[1]), "+f"(c[2]), "+f"(c[3]) : "r"(a0), "r"(a1), "r"(a2), "r"(a3), "r"(b0), "r"(b1));
}
__device__ __forceinline__ uint64_t desc_b(uint32_t addr, uint32_t lbo, uint32_t sbo, uint32_t sw) {
  return (uint64_t)((addr & 0x3FFFF) >> 4) | ((uint64_t)(lbo >> 4) << 16) | ((uint64_t)(sbo >> 4) << 32) | ((uint64_t)sw << 62);
}
#define WG_FENCE() asm volatile("wgmma.fence.sync.aligned;" ::: "memory")
#define WG_COMMIT() asm volatile("wgmma.commit_group.sync.aligned;" ::: "memory")
#define WG_WAIT(n) asm volatile("wgmma.wait_group.sync.aligned " #n ";" ::: "memory")
template <int N> __device__ __forceinline__ void reg_fence(float (&d)[N]) {
#pragma unroll
  for (int i = 0; i < N; i++) asm volatile("" : "+f"(d[i])::"memory");
}
constexpr uint32_t ONES = 0x3F803F80u;

__device__ __forceinline__ void wgmma_rs64(float (&d)[32], uint32_t a0, uint32_t a1, uint32_t a2, uint32_t a3, uint64_t db, int sd) {
  asm volatile("{\n.reg .pred p;\nsetp.ne.b32 p, %37, 0;\n"
    "wgmma.mma_async.sync.aligned.m64n64k16.f32.bf16.bf16 "
    "{%0, %1, %2, %3, %4, %5, %6, %7, %8, %9, %10, %11, %12, %13, %14, %15, %16, %17, %18, %19, %20, %21, %22, %23, %24, %25, %26, %27, %28, %29, %30, %31}, "
    "{%32,%33,%34,%35}, %36, p, 1, 1, 1;\n}\n"
    : "+f"(d[0]), "+f"(d[1]), "+f"(d[2]), "+f"(d[3]), "+f"(d[4]), "+f"(d[5]), "+f"(d[6]), "+f"(d[7]),
      "+f"(d[8]), "+f"(d[9]), "+f"(d[10]), "+f"(d[11]), "+f"(d[12]), "+f"(d[13]), "+f"(d[14]), "+f"(d[15]),
      "+f"(d[16]), "+f"(d[17]), "+f"(d[18]), "+f"(d[19]), "+f"(d[20]), "+f"(d[21]), "+f"(d[22]), "+f"(d[23]),
      "+f"(d[24]), "+f"(d[25]), "+f"(d[26]), "+f"(d[27]), "+f"(d[28]), "+f"(d[29]), "+f"(d[30]), "+f"(d[31])
    : "r"(a0), "r"(a1), "r"(a2), "r"(a3), "l"(db), "r"(sd));
}

__device__ __forceinline__ void wgmma_rs128(float (&d)[64], uint32_t a0, uint32_t a1, uint32_t a2, uint32_t a3, uint64_t db, int sd) {
  asm volatile("{\n.reg .pred p;\nsetp.ne.b32 p, %69, 0;\n"
    "wgmma.mma_async.sync.aligned.m64n128k16.f32.bf16.bf16 "
    "{%0, %1, %2, %3, %4, %5, %6, %7, %8, %9, %10, %11, %12, %13, %14, %15, %16, %17, %18, %19, %20, %21, %22, %23, %24, %25, %26, %27, %28, %29, %30, %31, %32, %33, %34, %35, %36, %37, %38, %39, %40, %41, %42, %43, %44, %45, %46, %47, %48, %49, %50, %51, %52, %53, %54, %55, %56, %57, %58, %59, %60, %61, %62, %63}, "
    "{%64,%65,%66,%67}, %68, p, 1, 1, 1;\n}\n"
    : "+f"(d[0]), "+f"(d[1]), "+f"(d[2]), "+f"(d[3]), "+f"(d[4]), "+f"(d[5]), "+f"(d[6]), "+f"(d[7]),
      "+f"(d[8]), "+f"(d[9]), "+f"(d[10]), "+f"(d[11]), "+f"(d[12]), "+f"(d[13]), "+f"(d[14]), "+f"(d[15]),
      "+f"(d[16]), "+f"(d[17]), "+f"(d[18]), "+f"(d[19]), "+f"(d[20]), "+f"(d[21]), "+f"(d[22]), "+f"(d[23]),
      "+f"(d[24]), "+f"(d[25]), "+f"(d[26]), "+f"(d[27]), "+f"(d[28]), "+f"(d[29]), "+f"(d[30]), "+f"(d[31]),
      "+f"(d[32]), "+f"(d[33]), "+f"(d[34]), "+f"(d[35]), "+f"(d[36]), "+f"(d[37]), "+f"(d[38]), "+f"(d[39]),
      "+f"(d[40]), "+f"(d[41]), "+f"(d[42]), "+f"(d[43]), "+f"(d[44]), "+f"(d[45]), "+f"(d[46]), "+f"(d[47]),
      "+f"(d[48]), "+f"(d[49]), "+f"(d[50]), "+f"(d[51]), "+f"(d[52]), "+f"(d[53]), "+f"(d[54]), "+f"(d[55]),
      "+f"(d[56]), "+f"(d[57]), "+f"(d[58]), "+f"(d[59]), "+f"(d[60]), "+f"(d[61]), "+f"(d[62]), "+f"(d[63])
    : "r"(a0), "r"(a1), "r"(a2), "r"(a3), "l"(db), "r"(sd));
}

__device__ __forceinline__ void wgmma_rs96(float (&d)[48], uint32_t a0, uint32_t a1, uint32_t a2, uint32_t a3, uint64_t db, int sd) {
  asm volatile("{\n.reg .pred p;\nsetp.ne.b32 p, %53, 0;\n"
    "wgmma.mma_async.sync.aligned.m64n96k16.f32.bf16.bf16 "
    "{%0, %1, %2, %3, %4, %5, %6, %7, %8, %9, %10, %11, %12, %13, %14, %15, %16, %17, %18, %19, %20, %21, %22, %23, %24, %25, %26, %27, %28, %29, %30, %31, %32, %33, %34, %35, %36, %37, %38, %39, %40, %41, %42, %43, %44, %45, %46, %47}, "
    "{%48,%49,%50,%51}, %52, p, 1, 1, 1;\n}\n"
    : "+f"(d[0]), "+f"(d[1]), "+f"(d[2]), "+f"(d[3]), "+f"(d[4]), "+f"(d[5]), "+f"(d[6]), "+f"(d[7]),
      "+f"(d[8]), "+f"(d[9]), "+f"(d[10]), "+f"(d[11]), "+f"(d[12]), "+f"(d[13]), "+f"(d[14]), "+f"(d[15]),
      "+f"(d[16]), "+f"(d[17]), "+f"(d[18]), "+f"(d[19]), "+f"(d[20]), "+f"(d[21]), "+f"(d[22]), "+f"(d[23]),
      "+f"(d[24]), "+f"(d[25]), "+f"(d[26]), "+f"(d[27]), "+f"(d[28]), "+f"(d[29]), "+f"(d[30]), "+f"(d[31]),
      "+f"(d[32]), "+f"(d[33]), "+f"(d[34]), "+f"(d[35]), "+f"(d[36]), "+f"(d[37]), "+f"(d[38]), "+f"(d[39]),
      "+f"(d[40]), "+f"(d[41]), "+f"(d[42]), "+f"(d[43]), "+f"(d[44]), "+f"(d[45]), "+f"(d[46]), "+f"(d[47])
    : "r"(a0), "r"(a1), "r"(a2), "r"(a3), "l"(db), "r"(sd));
}

struct RowStats { float s[4], g0[4], g1[4]; };
__device__ __forceinline__ void stats_acc(RowStats& r, uint32_t a0, uint32_t a1, uint32_t a2, uint32_t a3) {
  mma16816(r.s, a0, a1, a2, a3, ONES, ONES);
  mma16816(r.g0, a0, a1, a2, a3, a0, a2);
  mma16816(r.g1, a0, a1, a2, a3, a1, a3);
}
__device__ __forceinline__ void stats_fin(const RowStats& r, int lane, float& s0, float& q0, float& s1, float& q1) {
  int g = lane >> 2, src = (lane & ~3) | (g >> 1);
  s0 = r.s[0]; s1 = r.s[2];
  q0 = __shfl_sync(~0u, (g & 1) ? r.g0[1] : r.g0[0], src);
  q1 = __shfl_sync(~0u, (g & 1) ? r.g1[3] : r.g1[2], src);
}
__device__ __forceinline__ void ln_coef(float s, float q, uint32_t& mul, uint32_t& add) {
  float mu = s * (1.f / D_);
  float var = fmaxf(q * (1.f / D_) - mu * mu, 0.f);
  float rs = rsqrtf(var + 1e-5f);
  mul = pack_bf16(rs, rs);
  float t = -mu * bf_lo(mul);
  add = pack_bf16(t, t);
}
__device__ __forceinline__ float silu_bf16(__nv_bfloat16 c) {
  float cv = __bfloat162float(c);
  float s = __fdividef(cv, 1.f + __expf(-cv));
  s = cv < -80.f ? -0.f : s;
  return bf_lo(pack_bf16(s, s));
}
__device__ __forceinline__ void mod_acc(float (&acc)[8], uint4 w, float s) {
  acc[0] += s * bf_lo(w.x); acc[1] += s * bf_hi(w.x); acc[2] += s * bf_lo(w.y); acc[3] += s * bf_hi(w.y);
  acc[4] += s * bf_lo(w.z); acc[5] += s * bf_hi(w.z); acc[6] += s * bf_lo(w.w); acc[7] += s * bf_hi(w.w);
}
template <int LO> __device__ __forceinline__ float mod_reduce(float (&a)[8], int lane) {
  bool h = lane & (4 << LO);
#pragma unroll
  for (int i = 0; i < 4; i++) a[i] = (h ? a[i + 4] : a[i]) + __shfl_xor_sync(~0u, h ? a[i] : a[i + 4], 4 << LO);
  h = lane & (2 << LO);
#pragma unroll
  for (int i = 0; i < 2; i++) a[i] = (h ? a[i + 2] : a[i]) + __shfl_xor_sync(~0u, h ? a[i] : a[i + 2], 2 << LO);
  h = lane & (1 << LO);
  return (h ? a[1] : a[0]) + __shfl_xor_sync(~0u, h ? a[0] : a[1], 1 << LO);
}
template <int N> __device__ __forceinline__ void mod_load(uint4 (&v)[N], const uint32_t* p, int stride) {
#pragma unroll
  for (int i = 0; i < N; i++) v[i] = ld_rlx4(p + (i & 3) * stride + (i >> 2) * D_);
}
template <int STRIDE> __device__ __forceinline__ void mod_poll(uint4 (&v)[4], const uint32_t* p, uint32_t par) {
  asm volatile("{\n.reg .pred p, e;\n.reg .u32 n, t;\nmov.u32 n, 0;\nLW:\nmov.u32 t, 0;\n"
               "lop3.b32 t, t, %0, %17, 0xF6;\nlop3.b32 t, t, %1, %17, 0xF6;\nlop3.b32 t, t, %2, %17, 0xF6;\nlop3.b32 t, t, %3, %17, 0xF6;\nlop3.b32 t, t, %4, %17, 0xF6;\nlop3.b32 t, t, %5, %17, 0xF6;\nlop3.b32 t, t, %6, %17, 0xF6;\nlop3.b32 t, t, %7, %17, 0xF6;\nlop3.b32 t, t, %8, %17, 0xF6;\nlop3.b32 t, t, %9, %17, 0xF6;\nlop3.b32 t, t, %10, %17, 0xF6;\nlop3.b32 t, t, %11, %17, 0xF6;\nlop3.b32 t, t, %12, %17, 0xF6;\nlop3.b32 t, t, %13, %17, 0xF6;\nlop3.b32 t, t, %14, %17, 0xF6;\nlop3.b32 t, t, %15, %17, 0xF6;\n"
               "and.b32 t, t, 1;\nsetp.eq.u32 p, t, 0;\nvote.sync.all.pred p, p, 0xffffffff;\n@p bra.uni LD;\n" BACKOFF
               "add.u32 n, n, 1;\nsetp.gt.u32 e, n, 4194304;\n@e trap;\n"
               "ld.relaxed.gpu.global.v4.u32 {%0,%1,%2,%3}, [%16+%18*0];\nld.relaxed.gpu.global.v4.u32 {%4,%5,%6,%7}, [%16+%18*1];\nld.relaxed.gpu.global.v4.u32 {%8,%9,%10,%11}, [%16+%18*2];\nld.relaxed.gpu.global.v4.u32 {%12,%13,%14,%15}, [%16+%18*3];\n"
               "bra.uni LW;\nLD:\n}" : "+r"(v[0].x), "+r"(v[0].y), "+r"(v[0].z), "+r"(v[0].w), "+r"(v[1].x), "+r"(v[1].y), "+r"(v[1].z), "+r"(v[1].w), "+r"(v[2].x), "+r"(v[2].y), "+r"(v[2].z), "+r"(v[2].w), "+r"(v[3].x), "+r"(v[3].y), "+r"(v[3].z), "+r"(v[3].w) : "l"(p), "r"(par), "n"(STRIDE * 4) : "memory");
}
__device__ __forceinline__ float4 mod_sum(const uint4* v) {
  float4 r = make_float4(0.f, 0.f, 0.f, 0.f);
#pragma unroll
  for (int i = 0; i < 4; i++) {
    r.x += __uint_as_float(v[i].x & ~1u); r.y += __uint_as_float(v[i].y & ~1u);
    r.z += __uint_as_float(v[i].z & ~1u); r.w += __uint_as_float(v[i].w & ~1u);
  }
  uint32_t a = pack_bf16(r.x, r.y), c = pack_bf16(r.z, r.w);
  return make_float4(bf_lo(a), bf_hi(a), bf_lo(c), bf_hi(c));
}
__device__ __forceinline__ float4 mod_gather(const uint32_t* p, uint32_t par) {
  uint4 v[4];
  mod_load(v, p, 4 * D_);
  mod_poll<4 * D_>(v, p, par);
  return mod_sum(v);
}
__device__ __forceinline__ void tab_store(uint32_t tab, int col, bool is_scale, float4 u) {
  const float o = is_scale ? 1.f : 0.f;
  uint32_t base = tab + (col >> 4) * 64 + ((col & 7) >> 1) * 16 + ((col >> 3) & 1) * 4 + (is_scale ? 0 : 8);
  sts1(base, pack_bf16(u.x + o, u.y + o));
  sts1(base + 16, pack_bf16(u.z + o, u.w + o));
}

__device__ __forceinline__ int k_chunk(int c, int bj) { return c < 2 ? bj ^ c : (c + (bj & 6)) & 7; }

struct Params {
  const __nv_bfloat16 *x, *wqkv, *wo, *w1, *w2, *c, *wmod;
  __nv_bfloat16* out;
  Scratch* scr;
};

__global__ void __launch_bounds__(384, 1)
fused_block_kernel(const __grid_constant__ CUtensorMap tm_x, const __grid_constant__ CUtensorMap tm_wqkv,
                   const __grid_constant__ CUtensorMap tm_wo, const __grid_constant__ CUtensorMap tm_w1a,
                   const __grid_constant__ CUtensorMap tm_w1b, const __grid_constant__ CUtensorMap tm_w2,
                   const __grid_constant__ CUtensorMap tm_xs, const Params p) {
  extern __shared__ __align__(1024) uint8_t smem_raw[];
  const uint32_t sm = (uint32_t)__cvta_generic_to_shared(smem_raw);
  const int tid = threadIdx.x, lane = tid & 31, warp = __shfl_sync(~0u, tid >> 5, 0);
  const int b = blockIdx.x;
  const int bi = b >> 3, bj = b & 7;
  Scratch& G = *p.scr;
  auto bar = [&](int i) { return sm + SM_BAR + 8 * i; };
  TS(0);
  uint4 mw0, mw1; __nv_bfloat16 mc0, mc1;
  if (warp < 8) {
    const int r = (b >> 5) * 128 + (tid >> 2);
    const __nv_bfloat16* wp = p.wmod + (size_t)r * (6 * D_) + (b & 31) * 32 + (tid & 3) * 8;
    mw0 = ld_nc4(wp); mw1 = ld_nc4(wp + 64 * 6 * D_);
    mc0 = p.c[r]; mc1 = p.c[r + 64];
  } else if (warp == 8) {
    if (lane == 0) {
#pragma unroll
      for (int c = 0; c < 8; c++) mbar_init(bar(B_FX + c), 1);
      asm volatile("fence.mbarrier_init.release.cluster;" ::: "memory");
#pragma unroll
      for (int c = 0; c < 8; c++) { mbar_expect(bar(B_FX + c), 16 * KB); tma3d(sm + x_off(c), &tm_x, 0, bi * 128 + (c >> 2) * 64, (c & 3) * 2, bar(B_FX + c)); }
    }
  } else if (tid == 288) {
    for (int r = 0; r < 4; r++) l2_prefetch(p.wqkv + (size_t)(b * 4 + r) * (3 * D_) + D_, KB);
  } else if (tid == 320) {
#pragma unroll
    for (int i = 8; i < 31; i++) mbar_init(bar(i), bar_count(i));
    asm volatile("fence.mbarrier_init.release.cluster;" ::: "memory");
  } else if (tid == 352) {
    if (sm & 1023) __trap();
#pragma unroll
    for (int i = 31; i < B_COUNT; i++) mbar_init(bar(i), bar_count(i));
    asm volatile("fence.mbarrier_init.release.cluster;" ::: "memory");
  }
  uint32_t ep;
  if (warp < 8) ep = ld_rlx(&G.epoch[b][lane]);
  auto get_tag = [&]() { uint32_t t; asm volatile("add.u32 %0, %1, 1;" : "=r"(t) : "r"(ep) : "memory"); return t; };
  __syncthreads();

  if (warp >= 8) {
    asm volatile("setmaxnreg.dec.sync.aligned.u32 40;");
    ep = ld_rlx(&G.epoch[b][lane]);
    if (warp == 8) {
      auto load_w1 = [&](int c) {
        mbar_expect(bar(B_FS + c), SLOT);
        int cb = bj * 224, kr = k_chunk(c, bj) * 64;
        tma3d(sm + c * SLOT, &tm_w1a, 0, kr, (cb + ((bj & 1) ? 96 : 0)) >> 6, bar(B_FS + c));
        tma3d(sm + c * SLOT + 16 * KB, &tm_w1b, 0, kr, (cb + ((bj & 1) ? 0 : 128)) >> 5, bar(B_FS + c));
      };
      uint32_t tag;
      auto load_nb = [&](int kv, uint32_t dst, int fb) {
        int nb = bi - 2 + (lane & 1);
        if (bi > 0) warp_wait_flags(&G.fkv[kv][nb < 0 ? 0 : nb][bj][0], tag);
        for (int n = 0; n < 2; n++)
          if (bi - 2 + n < 0)
            for (int o = lane * 16; o < 16 * (int)KB; o += 512) sts4(dst + n * 16 * KB + o, 0, 0, 0, 0);
        __syncwarp();
        if (lane == 0) {
          asm volatile("fence.proxy.async.global;" ::: "memory");
          mbar_expect(bar(fb), (bi >= 2 ? 32 : 16 * bi) * KB);
          for (int n = 0; n < 2; n++)
            if (bi - 2 + n >= 0) bulk_ld(dst + n * 16 * KB, G.kv[kv][bi - 2 + n][bj], 16 * KB, bar(fb));
        }
        __syncwarp();
      };
      auto load_w = [&](int i, uint32_t dst, int col) { mbar_expect(bar(B_FW + i), 32 * KB); tma2d(sm + dst, &tm_wqkv, col + bj * 64, (i & 1) * 256, bar(B_FW + i)); };
      if (lane == 0) {
        mbar_wait(bar(B_FX + 5), 0); load_w(0, SM_WK0, 512);
        for (int r = 0; r < 4; r++) l2_prefetch(p.wqkv + (size_t)(b * 4 + r) * (3 * D_) + 2 * D_, KB);
        mbar_wait(bar(B_FX + 7), 0);
        TS(2);
        for (int r = 0; r < 4; r++) l2_prefetch(p.wmod + (size_t)(b * 4 + r) * (6 * D_) + 2 * D_, 4 * KB);
        for (int r = 0; r < 4; r++) l2_prefetch(p.wqkv + (size_t)(b * 4 + r) * (3 * D_), KB);
        mbar_wait(bar(B_FW + 0), 0); load_w(1, SM_WK1, 512);
        TS(3);
        mbar_wait(bar(B_RED), 0);
        mbar_wait(bar(B_TAB1), 0); load_w(2, SM_WV, 1024);
        mbar_wait(bar(B_FW + 1), 0); mbar_wait(bar(B_XFREE), 0); load_w(3, SM_WV + 32 * KB, 1024);
        mbar_wait(bar(B_FW + 2), 0); load_w(4, SM_WQ, 0);
        mbar_wait(bar(B_FW + 3), 0); load_w(5, SM_WQ + 32 * KB, 0);
      }
      __syncwarp();
      tag = get_tag();
      mbar_wait(bar(B_EW + 0), 0);
      TS(5);
      load_nb(0, sm + SM_K, B_FKN);
      TS(6);
      load_nb(1, sm + SM_V, B_FVN);
      TS(7);
      if (lane == 0) {
        l2_prefetch(p.w1 + (size_t)b * 7168, 14336);
        l2_prefetch(p.w2 + (size_t)b * 7168, 14336);
        mbar_wait(bar(B_EW + 2), 0);
        mbar_expect(bar(B_FWO), 64 * KB);
        tma2d(sm + SM_WQ, &tm_wo, bj * 64, 0, bar(B_FWO));
        tma2d(sm + SM_WQ + 32 * KB, &tm_wo, bj * 64, 256, bar(B_FWO));
      }
      __syncwarp();
      for (int w = 0; w < 2; w++) {
        warp_wait_flags(&G.fo[bi][w][lane & 7], tag);
        if (lane == 0) {
          asm volatile("fence.proxy.async.global;" ::: "memory");
          mbar_expect(bar(B_FO + w), 32 * KB);
          bulk_ld(sm + w * 32 * KB, G.o[bi][w], 32 * KB, bar(B_FO + w));
        }
        __syncwarp();
      }
      TS(10);
      if (lane == 0) {
        mbar_wait(bar(B_XFREE), 1);
        mbar_expect(bar(B_FX), 16 * KB);
        tma2d(sm + SM_K, &tm_xs, bj * 64, bi * 128, bar(B_FX));
        mbar_wait(bar(B_EO), 0);
        load_w1(0);
#pragma unroll 1
        for (int c = 1; c < 8; c++) {
          if (c == G1) mbar_wait(bar(B_EWO), 0);
          if (c == G2) mbar_wait(bar(B_ATT), 0);
          if (c >= W1D) mbar_wait(bar(B_FS + c - W1D), 0);
          load_w1(c);
          if (c == 4) TS(15);
        }
        TS(16);
        for (int c = 0; c < 8; c++) {
          mbar_wait(bar(B_ES + c), 0);
          mbar_wait(bar(B_FS + ((c + 8 - W2D) & 7)), c >= W2D);
          if (c == 3) TS(17);
          mbar_expect(bar(B_FS + c), SLOT);
          tma2d(sm + c * SLOT, &tm_w2, c * 64, bj * 224, bar(B_FS + c));
        }
      }
      __syncwarp(); TS(22); TSDUMP();
    } else if (warp < 11) {
      mbar_wait(bar(B_RED2), 0);
      const uint32_t par = get_tag() & 1;
      const float* red = reinterpret_cast<const float*>(smem_raw + SM_RED2) + (warp - 9) * 32 + lane;
      float t = 0.f;
#pragma unroll
      for (int w = 0; w < 8; w++) t += red[w * 64];
      st_rlx(&G.mod2[b >> 5][(b & 31) * 64 + (warp - 9) * 32 + lane], (__float_as_uint(t) & ~1u) | par);
      warp_arrive(bar(B_RED3));
      TS(1);
      mbar_wait(bar(B_RED3), 0);
#pragma unroll 1
      for (int m = 0; m < 4; m++) {
        int i4 = (m * 32 + lane) * 4;
        tab_store(sm + SM_TAB, i4, warp == 10, mod_gather(&G.mod2[0][(warp - 8) * D_ + i4], par));
      }
#pragma unroll 1
      for (int m = 0; m < 3; m++) {
        int i4 = m == 0 ? bj * 64 + (lane & 15) * 4 : D_ + (((warp - 9) * 2 + m - 1) * 32 + lane) * 4;
        *reinterpret_cast<float4*>(&G.gate[b][i4]) = mod_gather(&G.mod2[0][i4 + (m ? 2 * D_ : 0)], par);
      }
      warp_arrive(bar(B_TAB2));
      TS(3); TSDUMP();
    } else {
      const uint32_t tag = get_tag();
      if (lane == 0) {
        mbar_wait(bar(B_KST), 0); st_rel(&G.fkv[0][bi][bj][0], tag);
        mbar_wait(bar(B_KVA), 0); mbar_wait(bar(B_KVB), 0); st_rel(&G.fkv[1][bi][bj][0], tag);
        mbar_wait(bar(B_OST), 0); st_rel(&G.fo[bi][0][bj], tag);
        mbar_wait(bar(B_OST + 1), 0); st_rel(&G.fo[bi][1][bj], tag);
        mbar_wait(bar(B_XST), 0); st_rel(&G.fx[bi][bj], tag);
      }
      __syncwarp();
      st_rlx(&G.epoch[b][lane], tag);
      warp_wait_flags(&G.fx[bi][lane & 7], tag);
      warp_arrive(bar(B_XOK));
    }
  } else {
    asm volatile("setmaxnreg.inc.sync.aligned.u32 232;");
    const int wg = warp >> 2, g = lane >> 2, q = lane & 3;
    const float sl0 = silu_bf16(mc0), sl1 = silu_bf16(mc1);
    uint32_t par;
    {
      float acc[8] = {};
      mod_acc(acc, mw0, sl0); mod_acc(acc, mw1, sl1);
      float v = mod_reduce<2>(acc, lane);
      TS(27);
      sts1(sm + SM_RED + (warp * 32 + q * 8 + g) * 4, __float_as_uint(v));
      asm volatile("bar.sync 1, 256;" ::: "memory");
      const float* red = reinterpret_cast<const float*>(smem_raw + SM_RED);
      float t = 0.f;
#pragma unroll
      for (int w = 0; w < 8; w++) t += red[w * 32 + lane];
      par = get_tag() & 1;
      st_rlx(&G.mod1[warp][b >> 5][(b & 31) * 32 + lane], (__float_as_uint(t) & ~1u) | par);
      warp_arrive(bar(B_RED));
    }
    TS(1);
    uint32_t qf[16];
    {
      uint32_t a[128];
      RowStats rs = {};
      const int lrow = (warp & 3) * 16 + (lane & 15);
#pragma unroll
      for (int c = 0; c < 4; c++) {
        mbar_wait(bar(B_FX + wg * 4 + c), 0);
        const uint32_t xb = sm + (wg ? x_off(4 + c) : x_off(c)) + lrow * 128;
#pragma unroll
        for (int k = 0; k < 8; k++) {
          uint32_t ad = xb + (k >> 2) * 8 * KB + (((2 * (k & 3) + (lane >> 4)) ^ (lane & 7)) << 4);
          int i = (c * 8 + k) * 4;
          asm volatile("ldmatrix.sync.aligned.m8n8.x4.shared.b16 {%0,%1,%2,%3}, [%4];" : "=r"(a[i]), "=r"(a[i + 1]), "=r"(a[i + 2]), "=r"(a[i + 3]) : "r"(ad) : "memory");
          stats_acc(rs, a[i], a[i + 1], a[i + 2], a[i + 3]);
        }
      }
      float s0, q0, s1, q1; uint32_t m0, d0, m1, d1;
      uint4 v[4];
      mod_load(v, &G.mod1[(b >> 1) & 7][0][tid * 4], 2 * D_);
      stats_fin(rs, lane, s0, q0, s1, q1);
      warp_arrive(bar(B_XFREE));
      TS(2);
      ln_coef(s0, q0, m0, d0); ln_coef(s1, q1, m1, d1);
      mod_poll<2 * D_>(v, &G.mod1[(b >> 1) & 7][0][tid * 4], par);
      tab_store(sm + SM_TAB, (tid & 127) * 4, wg, mod_sum(v));
      warp_arrive(bar(B_TAB1));
#pragma unroll
      for (int i = 0; i < 128; i += 2) { hfma2v(a[i], m0, d0); hfma2v(a[i + 1], m1, d1); }
      mbar_wait(bar(B_TAB1), 0);
      TS(3);
      uint4 m2[4] = {};
      if (wg == 1) asm volatile("bar.sync 5, 256;" ::: "memory");
#pragma unroll
      for (int k0 = 0; k0 < 32; k0 += 8) {
        uint4 t[8];
#pragma unroll
        for (int k = 0; k < 8; k++) t[k] = lds4(sm + SM_TAB + (k0 + k) * 64 + q * 16);
#pragma unroll
        for (int k = 0; k < 8; k++) {
          const int i = 4 * (k0 + k);
          hfma2v(a[i], t[k].x, t[k].z); hfma2v(a[i + 1], t[k].x, t[k].z); hfma2v(a[i + 2], t[k].y, t[k].w); hfma2v(a[i + 3], t[k].y, t[k].w);
        }
      }
      if (wg == 0) asm volatile("bar.arrive 5, 256;" ::: "memory");
      TS(4);
#pragma unroll 1
      for (int ch = 0; ch < 3; ch++) {
        float acc[32];
        const uint32_t w0 = sm + (ch == 0 ? SM_WK0 : (ch == 1 ? SM_WV : SM_WQ));
        const uint32_t w1 = sm + (ch == 0 ? SM_WK1 : (ch == 1 ? SM_WV + 32 * KB : SM_WQ + 32 * KB));
        if (wg == 1 || ch > 0) asm volatile("bar.sync %0, 256;" ::"r"(3 + wg) : "memory");
        mbar_wait(bar(B_FW + 2 * ch), 0);
        WG_FENCE();
#pragma unroll
        for (int k = 0; k < 16; k++) wgmma_rs64(acc, a[4 * k], a[4 * k + 1], a[4 * k + 2], a[4 * k + 3], desc_b(w0 + k * 2048, 0, 1024, 1), k != 0);
        mbar_wait(bar(B_FW + 2 * ch + 1), 0);
        WG_FENCE();
#pragma unroll
        for (int k = 16; k < 32; k++) wgmma_rs64(acc, a[4 * k], a[4 * k + 1], a[4 * k + 2], a[4 * k + 3], desc_b(w1 + (k - 16) * 2048, 0, 1024, 1), 1);
        WG_COMMIT();
        if (wg == 0 || ch < 2) asm volatile("bar.arrive %0, 256;" ::"r"(4 - wg) : "memory");
        if (ch == 0) {
        const __nv_bfloat16* wp = p.wmod + (size_t)((b >> 5) * 128 + (tid >> 2)) * (6 * D_) + 2 * D_ + (b & 31) * 64 + q * 8;
        m2[0] = ld_nc4(wp); m2[1] = ld_nc4(wp + 32); m2[2] = ld_nc4(wp + 64 * 6 * D_); m2[3] = ld_nc4(wp + 64 * 6 * D_ + 32);
      }
        mbar_wait(bar(B_XFREE), 0);
        if (ch == 1) {
#pragma unroll
          for (int u = 0; u < 4; u++) asm volatile("" : "+r"(m2[u].x), "+r"(m2[u].y), "+r"(m2[u].z), "+r"(m2[u].w));
#pragma unroll
          for (int u = 0; u < 2; u++) {
            float ma[8] = {};
            mod_acc(ma, m2[u], sl0); mod_acc(ma, m2[2 + u], sl1);
            sts1(sm + SM_RED2 + (warp * 64 + u * 32 + q * 8 + g) * 4, __float_as_uint(mod_reduce<2>(ma, lane)));
          }
          warp_arrive(bar(B_RED2));
        }
        WG_WAIT(0);
        reg_fence(acc);
        warp_arrive(bar(B_EW + ch));
#pragma unroll
        for (int h = 0; h < 4; h++) {
          qf[4 * h] = pack_bf16(acc[8 * h], acc[8 * h + 1]); qf[4 * h + 1] = pack_bf16(acc[8 * h + 2], acc[8 * h + 3]);
          qf[4 * h + 2] = pack_bf16(acc[8 * h + 4], acc[8 * h + 5]); qf[4 * h + 3] = pack_bf16(acc[8 * h + 6], acc[8 * h + 7]);
        }
        if (ch < 2) {
          const uint32_t dst = sm + (ch == 0 ? SM_K : SM_V) + 32 * KB + warp * 2048 + lane * 16;
          uint4* gdst = &G.kv[ch][bi][bj][warp * 128 + lane];
#pragma unroll
          for (int h = 0; h < 4; h++) {
            uint32_t r0 = qf[4 * h], r1 = qf[4 * h + 2], r2 = qf[4 * h + 1], r3 = qf[4 * h + 3];
            if (ch == 1) { r0 = movm(qf[4 * h]); r1 = movm(qf[4 * h + 1]); r2 = movm(qf[4 * h + 2]); r3 = movm(qf[4 * h + 3]); }
            stg4(gdst + h * 32, r0, r1, r2, r3);
            sts4(dst + h * 512, r0, r1, r2, r3);
          }
          warp_arrive(bar(ch == 1 ? B_KVA + wg : B_KST));
        }
        TS(5 + ch);
      }
    }
    {
      mbar_wait(bar(B_KVA), 0);
      if (wg == 1) mbar_wait(bar(B_KVB), 0);
      mbar_wait(bar(B_FKN), 0);
      TS(8);
      const float sc = 0.25f * 1.4426950408889634f;
      const int tmin = 16 - 8 * bi - warp;
      const bool v00 = 2 * q <= g, v01 = 2 * q + 1 <= g;
      float s[16][2][4], mx0[16], mx1[16], b0, b1;
      const uint32_t zero = blockIdx.y;
      uint32_t kb = sm + SM_K + warp * 2048 + lane * 16;
      auto scores = [&](int t) {
        uint4 kf = lds4(kb + t * 2048);
        float init = t < tmin ? -INFINITY : 0.f;
#pragma unroll
        for (int e = 0; e < 4; e++) { s[t][0][e] = init; s[t][1][e] = init; }
        mma16816(s[t][0], qf[0], qf[1], qf[2], qf[3], kf.x, kf.y);
        mma16816(s[t][1], qf[0], qf[1], qf[2], qf[3], kf.z, kf.w);
        if (t == 0) {
          uint4 kd = lds4(kb + 16 * 2048);
          float sd0[4] = {}, sd1[4] = {};
          mma16816(sd0, qf[0], qf[1], qf[2], qf[3], kd.x, kd.y);
          mma16816(sd1, qf[0], qf[1], qf[2], qf[3], kd.z, kd.w);
          s[0][0][0] = v00 ? sd0[0] : s[0][0][0]; s[0][0][1] = v01 ? sd0[1] : s[0][0][1];
          s[0][0][2] = sd0[2]; s[0][0][3] = sd0[3];
          s[0][1][2] = v00 ? sd1[2] : s[0][1][2]; s[0][1][3] = v01 ? sd1[3] : s[0][1][3];
        }
        mx0[t] = fmaxf(fmaxf(s[t][0][0], s[t][0][1]), fmaxf(s[t][1][0], s[t][1][1]));
        mx1[t] = fmaxf(fmaxf(s[t][0][2], s[t][0][3]), fmaxf(s[t][1][2], s[t][1][3]));
        if (t > 0) { mx0[t] = fmaxf(mx0[t], mx0[t - 1]); mx1[t] = fmaxf(mx1[t], mx1[t - 1]); }
      };
      auto rowmax = [&]() {
        float m0 = mx0[15], m1 = mx1[15];
        m0 = fmaxf(m0, __shfl_xor_sync(~0u, m0, 1)); m1 = fmaxf(m1, __shfl_xor_sync(~0u, m1, 1));
        m0 = fmaxf(m0, __shfl_xor_sync(~0u, m0, 2)); m1 = fmaxf(m1, __shfl_xor_sync(~0u, m1, 2));
        b0 = -m0 * sc; b1 = -m1 * sc;
      };
#pragma unroll
      for (int t = 0; t < 16; t++) scores(t);
      rowmax();
      mbar_wait(bar(B_FVN), 0);
#pragma unroll 1
      for (int h = 0; h < 4; h++) {
        const uint32_t vb = kb + (SM_V - SM_K);
        kb += h < 3 ? 512 : 0;
#pragma unroll
        for (int i = 0; i < 12; i++) qf[i] = qf[i + 4];
        float o0[4] = {}, o1[4] = {}, l[4] = {};
#pragma unroll
        for (int t = 0; t < 16; t++) {
          uint4 vf = lds4(vb + t * 2048);
          if (t >= DEP) {
            b0 = __uint_as_float(__float_as_uint(b0) | (__float_as_uint(mx0[t - DEP]) & zero));
            b1 = __uint_as_float(__float_as_uint(b1) | (__float_as_uint(mx1[t - DEP]) & zero));
          }
          uint32_t p0 = pack_bf16(ex2(fmaf(s[t][0][0], sc, b0)), ex2(fmaf(s[t][0][1], sc, b0)));
          uint32_t p1 = pack_bf16(ex2(fmaf(s[t][0][2], sc, b1)), ex2(fmaf(s[t][0][3], sc, b1)));
          uint32_t p2 = pack_bf16(ex2(fmaf(s[t][1][0], sc, b0)), ex2(fmaf(s[t][1][1], sc, b0)));
          uint32_t p3 = pack_bf16(ex2(fmaf(s[t][1][2], sc, b1)), ex2(fmaf(s[t][1][3], sc, b1)));
          mma16816(l, p0, p1, p2, p3, ONES, ONES);
          if (t == 0) {
            const uint32_t mk = (v00 ? 0xffffu : 0u) | (v01 ? 0xffff0000u : 0u);
            uint4 vd = lds4(vb + 16 * 2048);
            mma16816(o0, p0 & mk, p1, 0u, p3 & mk, vd.x, vd.y);
            mma16816(o1, p0 & mk, p1, 0u, p3 & mk, vd.z, vd.w);
            p0 &= ~mk; p1 = 0u; p3 &= ~mk;
          }
          mma16816(o0, p0, p1, p2, p3, vf.x, vf.y);
          mma16816(o1, p0, p1, p2, p3, vf.z, vf.w);
          scores(t);
        }
        rowmax();
        const float r0 = __fdividef(1.f, l[0]), r1 = __fdividef(1.f, l[2]);
        stg4(&G.o[bi][wg][h][warp & 3][bj][lane], pack_bf16(round_even(o0[0] * r0), o0[1] * r0) | (h >= 2 ? par : 0u), pack_bf16(o0[2] * r1, o0[3] * r1),
             pack_bf16(o1[0] * r0, o1[1] * r0), pack_bf16(o1[2] * r1, o1[3] * r1));
        if (h == 1 || h == 2) warp_arrive(bar(h == 1 ? B_OST + wg : B_XFREE));
        TS(9 + h);
      }
    }
    {
      uint4 a0[16], a2[8], a3[8];
      const uint4* op = &G.o[bi][wg][2][warp & 3][0][lane];
#pragma unroll
      for (int k = 0; k < 8; k++) a2[k] = ld_rlx4(op + k * 32);
      uint32_t xr[16]; float2 ga[8];
      mbar_wait(bar(B_FX), 1);
#pragma unroll
      for (int n = 0; n < 16; n++)
        asm volatile("ld.shared.u32 %0, [%1];" : "=r"(xr[n]) : "r"(sm + SM_K + (warp * 16 + (n & 1) * 8 + g) * 128 + (((n >> 1) ^ g) << 4) + q * 4) : "memory");
      mbar_wait(bar(B_FO + wg), 0);
#pragma unroll
      for (int k = 0; k < 16; k++) a0[k] = lds4(sm + wg * 32 * KB + (k >> 3) * 16 * KB + (warp & 3) * 4096 + (k & 7) * 512 + lane * 16);
      float acc[32];
      mbar_wait(bar(B_FWO), 0);
      WG_FENCE();
#pragma unroll
      for (int k = 0; k < 16; k++) wgmma_rs64(acc, a0[k].x, a0[k].y, a0[k].z, a0[k].w, desc_b(sm + SM_WQ + ((k & 7) * 4 + (k >> 3)) * 2048, 0, 1024, 1), k != 0);
      WG_COMMIT();
      warp_arrive(bar(B_EO));
      check_tags(a2, op, lane, par);
      WG_FENCE();
#pragma unroll
      for (int k = 0; k < 8; k++) wgmma_rs64(acc, a2[k].x, a2[k].y, a2[k].z, a2[k].w, desc_b(sm + SM_WQ + (k * 4 + 2) * 2048, 0, 1024, 1), 1);
      WG_COMMIT();
#pragma unroll
      for (int k = 0; k < 8; k++) a3[k] = ld_rlx4(op + 1024 + k * 32);
      mbar_wait(bar(B_TAB2), 0);
#pragma unroll
      for (int n = 0; n < 8; n++) asm volatile("ld.global.v2.f32 {%0,%1}, [%2];" : "=f"(ga[n].x), "=f"(ga[n].y) : "l"(&G.gate[b][bj * 64 + n * 8 + 2 * q]) : "memory");
      check_tags(a3, op + 1024, lane, par);
      TS(13);
      WG_FENCE();
#pragma unroll
      for (int k = 0; k < 8; k++) wgmma_rs64(acc, a3[k].x, a3[k].y, a3[k].z, a3[k].w, desc_b(sm + SM_WQ + (k * 4 + 3) * 2048, 0, 1024, 1), 1);
      WG_COMMIT();
      WG_WAIT(0);
      reg_fence(acc);
      warp_arrive(bar(B_EWO));
#pragma unroll
      for (int n = 0; n < 16; n++) asm volatile("" : "+r"(xr[n]));
      TS(14);
      RowStats rs = {};
      uint32_t r[4][4];
#pragma unroll
      for (int k = 0; k < 4; k++) {
        float f0 = 0.f, f1 = 0.f;
#pragma unroll
        for (int e = 3; e >= 0; e--) {
          int n = 2 * k + (e >> 1), i = 4 * n + 2 * (e & 1);
          uint32_t xv = xr[2 * n + (e & 1)];
          f0 = fmaf(ga[n].x, acc[i], bf_lo(xv)); f1 = fmaf(ga[n].y, acc[i + 1], bf_hi(xv));
          r[k][e] = pack_bf16(f0, f1);
        }
        stats_acc(rs, r[k][0], r[k][1], r[k][2], r[k][3]);
        stg4(&G.x1[bi][warp][bj * 4 + k][lane], pack_bf16(round_even(f0), f1) | par, r[k][1], r[k][2], r[k][3]);
      }
      float s0, q0, s1, q1;
      stats_fin(rs, lane, s0, q0, s1, q1);
      asm volatile("{\n.reg .pred p;\nsetp.eq.u32 p, %5, 0;\n@p st.global.v4.u32 [%0], {%1,%2,%3,%4};\n}" ::"l"(&G.st[bi][warp][bj][g]),
                   "r"((__float_as_uint(s0) & ~1u) | par), "r"(__float_as_uint(q0)), "r"(__float_as_uint(s1)), "r"(__float_as_uint(q1)), "r"(q) : "memory");
      stg4(G.x1e[bi][warp][bj][lane], r[0][0], r[1][0], r[2][0], r[3][0]);
      warp_arrive(bar(B_XST));
      TS(15);
    }
    uint32_t hid[56];
    {
      const uint4* xa = &G.x1[bi][warp][0][lane];
      uint4 st[2], raw[2][4];
#pragma unroll
      for (int k = 0; k < 4; k++) raw[0][k] = ld_rlx4(xa + (bj * 4 + k) * 32);
      asm volatile("{\n.reg .pred p, e;\n.reg .u32 n, t;\nmov.u32 n, 0;\nLW:\n"
                   "ld.relaxed.gpu.global.v4.u32 {%0,%1,%2,%3}, [%8];\nld.relaxed.gpu.global.v4.u32 {%4,%5,%6,%7}, [%8+512];\n"
                   "xor.b32 t, %0, %9;\nlop3.b32 t, t, %4, %9, 0xF6;\nand.b32 t, t, 1;\nsetp.eq.u32 p, t, 0;\nvote.sync.all.pred p, p, 0xffffffff;\n@p bra.uni LD;\n" BACKOFF
                   "add.u32 n, n, 1;\nsetp.gt.u32 e, n, 4194304;\n@e trap;\nbra.uni LW;\nLD:\n}"
                   : "=&r"(st[0].x), "=&r"(st[0].y), "=&r"(st[0].z), "=&r"(st[0].w), "=&r"(st[1].x), "=&r"(st[1].y), "=&r"(st[1].z), "=&r"(st[1].w)
                   : "l"(&G.st[bi][warp][0][lane]), "r"(par) : "memory");
      st[0].x &= ~1u; st[1].x &= ~1u;
      TS(16);
#pragma unroll
      for (int k = 0; k < 4; k++) raw[1][k] = ld_rlx4(xa + ((bj ^ 1) * 4 + k) * 32);
      warp_arrive(bar(B_ATT));
      const uint4 st0 = st[0], st1 = st[1];
      float s0 = __uint_as_float(st0.x) + __uint_as_float(st1.x), q0 = __uint_as_float(st0.y) + __uint_as_float(st1.y);
      float s1 = __uint_as_float(st0.z) + __uint_as_float(st1.z), q1 = __uint_as_float(st0.w) + __uint_as_float(st1.w);
#pragma unroll
      for (int o = 8; o < 32; o <<= 1) {
        s0 += __shfl_xor_sync(~0u, s0, o); q0 += __shfl_xor_sync(~0u, q0, o);
        s1 += __shfl_xor_sync(~0u, s1, o); q1 += __shfl_xor_sync(~0u, q1, o);
      }
      uint32_t m0, d0, m1, d1;
      ln_coef(s0, q0, m0, d0); ln_coef(s1, q1, m1, d1);
      m0 = __shfl_sync(~0u, m0, g); d0 = __shfl_sync(~0u, d0, g); m1 = __shfl_sync(~0u, m1, g); d1 = __shfl_sync(~0u, d1, g);
      float accA[64], accB[48];
      uint32_t an[2][16];
#pragma unroll 1
      for (int c2 = 0; c2 < 8; c2 += 2) {
#pragma unroll
        for (int u = 0; u < 2; u++) {
          const int c = c2 + u, kc = k_chunk(c, bj);
          check_tags(raw[u], xa + kc * 128, lane, par);
#pragma unroll
          for (int k = 0; k < 4; k++) {
            uint4 t = lds4(sm + SM_TAB + (kc * 4 + k) * 64 + q * 16);
            an[u][4 * k] = hfma2(hfma2(raw[u][k].x, m0, d0), t.x, t.z); an[u][4 * k + 1] = hfma2(hfma2(raw[u][k].y, m1, d1), t.x, t.z);
            an[u][4 * k + 2] = hfma2(hfma2(raw[u][k].z, m0, d0), t.y, t.w); an[u][4 * k + 3] = hfma2(hfma2(raw[u][k].w, m1, d1), t.y, t.w);
          }
          if (c2 < 6) {
#pragma unroll
            for (int k = 0; k < 4; k++) raw[u][k] = ld_rlx4(xa + (((c + 2 + (bj & 6)) & 7) * 4 + k) * 32);
          }
          mbar_wait(bar(B_FS + c), 0);
          WG_FENCE();
#pragma unroll
          for (int k = 0; k < 4; k++) {
            wgmma_rs128(accA, an[u][4 * k], an[u][4 * k + 1], an[u][4 * k + 2], an[u][4 * k + 3], desc_b(sm + c * SLOT + k * 2048, 8 * KB, 1024, 1), (c | k) != 0);
            wgmma_rs96(accB, an[u][4 * k], an[u][4 * k + 1], an[u][4 * k + 2], an[u][4 * k + 3], desc_b(sm + c * SLOT + 16 * KB + k * 1024, 4 * KB, 512, 2), (c | k) != 0);
          }
          WG_COMMIT();
          WG_WAIT(1);
          if (c > 0) warp_arrive(bar(B_ES + c - 1));
          if (u == 1) TS(23 + (c2 >> 1));
        }
      }
      WG_WAIT(0);
      reg_fence(accA); reg_fence(accB);
      warp_arrive(bar(B_ES + 7));
#pragma unroll
      for (int i = 0; i < 32; i++) hid[i] = pack_relu(accA[2 * i], accA[2 * i + 1]);
#pragma unroll
      for (int i = 0; i < 24; i++) hid[32 + i] = pack_relu(accB[2 * i], accB[2 * i + 1]);
      TS(17);
    }
    {
      const uint32_t offA = (bj & 1) ? 96 * 128 : 0, offB = (bj & 1) ? 0 : 128 * 128;
      const uint32_t eye = (g >> 1) == q ? (0x3F80u << ((g & 1) * 16)) : 0u;
      float acc[2][32];
      auto issue = [&](float (&d)[32], int c) {
        mbar_wait(bar(B_FS + c), 1);
        WG_FENCE();
#pragma unroll
        for (int k = 0; k < 14; k++)
          wgmma_rs64(d, hid[4 * k], hid[4 * k + 1], hid[4 * k + 2], hid[4 * k + 3],
                     desc_b(sm + c * SLOT + (k < 8 ? offA + k * 2048 : offB + (k - 8) * 2048), 0, 1024, 1), k != 0);
        WG_COMMIT();
      };
      auto store = [&](float (&d)[32], int c) {
        reg_fence(d);
#pragma unroll
        for (int k = 0; k < 4; k++)
          stg4(&G.part[bi][warp][c * 4 + k][bj][lane], pack_bf16(round_even(d[8 * k]), d[8 * k + 1]) | par, pack_bf16(d[8 * k + 2], d[8 * k + 3]),
               pack_bf16(d[8 * k + 4], d[8 * k + 5]), pack_bf16(d[8 * k + 6], d[8 * k + 7]));
      };
      uint4 v[8], xv; uint32_t xe; float2 g0, g1;
      auto fetch = [&](int s) {
#pragma unroll
        for (int u = 0; u < 8; u++) v[u] = ld_rlx4(&G.part[bi][bj][s][u][lane]);
        xv = ld_rlx4(&G.x1[bi][bj][s][lane]); xe = ld_rlx(&G.x1e[bi][bj][s >> 2][lane][s & 3]);
        g0 = *reinterpret_cast<const float2*>(&G.gate[b][D_ + s * 16 + 2 * q]); g1 = *reinterpret_cast<const float2*>(&G.gate[b][D_ + s * 16 + 8 + 2 * q]);
      };
      auto reduce = [&](int s) {
        check_tags(v, &G.part[bi][bj][s][0][lane], lane, par);
        float f[4] = {}, h[4] = {};
#pragma unroll
        for (int u = 0; u < 8; u++) { mma16816(f, v[u].x, v[u].y, v[u].z, v[u].w, eye, 0u); mma16816(h, v[u].x, v[u].y, v[u].z, v[u].w, 0u, eye); }
        uint32_t* op = reinterpret_cast<uint32_t*>(p.out + (size_t)(bi * 128 + bj * 16 + g) * D_ + s * 16 + 2 * q);
        op[0] = pack_bf16(fmaf(g0.x, f[0], bf_lo(xe)), fmaf(g0.y, f[1], bf_hi(xe)));
        op[4 * D_] = pack_bf16(fmaf(g0.x, f[2], bf_lo(xv.y)), fmaf(g0.y, f[3], bf_hi(xv.y)));
        op[4] = pack_bf16(fmaf(g1.x, h[0], bf_lo(xv.z)), fmaf(g1.y, h[1], bf_hi(xv.z)));
        op[4 * D_ + 4] = pack_bf16(fmaf(g1.x, h[2], bf_lo(xv.w)), fmaf(g1.y, h[3], bf_hi(xv.w)));
      };
      mbar_wait(bar(B_XOK), 0);
      issue(acc[0], 0);
#pragma unroll 1
      for (int cc = 0; cc < 4 + LAG; cc++) {
        const int s = (cc - LAG) * 8 + warp;
        if (cc < 4) {
          issue(acc[1], 2 * cc + 1);
        } else if (cc == SPIN) {
          spin_tag(&G.part[bi][bj][s][lane & 7][31], par);
        }
        if (cc >= LAG) fetch(s);
        if (cc < 4) {
          WG_WAIT(1);
          store(acc[0], 2 * cc);
          issue(acc[0], cc < 3 ? 2 * cc + 2 : 7);
          WG_WAIT(1);
          store(acc[1], 2 * cc + 1);
          TS(18 + cc);
        }
        if (cc >= LAG) reduce(s);
      }
      WG_WAIT(0);
      TS(22); TSDUMP();
    }
  }
}

typedef CUresult (*EncodeFn)(CUtensorMap*, CUtensorMapDataType, cuuint32_t, void*, const cuuint64_t*, const cuuint64_t*,
                             const cuuint32_t*, const cuuint32_t*, CUtensorMapInterleave, CUtensorMapSwizzle,
                             CUtensorMapL2promotion, CUtensorMapFloatOOBfill);

void make_map(EncodeFn enc, CUtensorMap* tm, const void* base, int rank, const cuuint64_t* dims, const cuuint64_t* strides,
              const cuuint32_t* box, CUtensorMapSwizzle sw) {
  cuuint32_t es[3] = {1, 1, 1};
  enc(tm, CU_TENSOR_MAP_DATA_TYPE_BFLOAT16, rank, const_cast<void*>(base), dims, strides, box, es,
      CU_TENSOR_MAP_INTERLEAVE_NONE, sw, CU_TENSOR_MAP_L2_PROMOTION_L2_128B, CU_TENSOR_MAP_FLOAT_OOB_FILL_NONE);
}
void make_map2(EncodeFn enc, CUtensorMap* tm, const void* base, int rows, int cols, int bc, int br, CUtensorMapSwizzle sw) {
  cuuint64_t dims[2] = {(cuuint64_t)cols, (cuuint64_t)rows}, strides[1] = {(cuuint64_t)cols * 2};
  cuuint32_t box[2] = {(cuuint32_t)bc, (cuuint32_t)br};
  make_map(enc, tm, base, 2, dims, strides, box, sw);
}

}

extern "C" void kernel_launch(void* const* d_in, const int* in_sizes, int n_in, void* d_out, int out_size) {
  EncodeFn enc = nullptr;
  cudaDriverEntryPointQueryResult qr;
  cudaGetDriverEntryPoint("cuTensorMapEncodeTiled", (void**)&enc, cudaEnableDefault, &qr);
  CUtensorMap tx, tqkv, two, tw1a, tw1b, tw2, txs;
  make_map2(enc, &txs, d_in[0], S_, D_, 64, 128, CU_TENSOR_MAP_SWIZZLE_128B);
  {
    cuuint64_t dims[3] = {64, (cuuint64_t)S_, D_ / 64}, strides[2] = {D_ * 2, 128};
    cuuint32_t box[3] = {64, 64, 2};
    make_map(enc, &tx, d_in[0], 3, dims, strides, box, CU_TENSOR_MAP_SWIZZLE_128B);
  }
  make_map2(enc, &tqkv, d_in[1], D_, 3 * D_, 64, 256, CU_TENSOR_MAP_SWIZZLE_128B);
  make_map2(enc, &two, d_in[2], D_, D_, 64, 256, CU_TENSOR_MAP_SWIZZLE_128B);
  {
    cuuint64_t dims[3] = {64, (cuuint64_t)D_, DFF / 64}, strides[2] = {DFF * 2, 128};
    cuuint32_t box[3] = {64, 64, 2};
    make_map(enc, &tw1a, d_in[4], 3, dims, strides, box, CU_TENSOR_MAP_SWIZZLE_128B);
    cuuint64_t dims2[3] = {32, (cuuint64_t)D_, DFF / 32}, strides2[2] = {DFF * 2, 64};
    cuuint32_t box2[3] = {32, 64, 3};
    make_map(enc, &tw1b, d_in[4], 3, dims2, strides2, box2, CU_TENSOR_MAP_SWIZZLE_64B);
  }
  make_map2(enc, &tw2, d_in[5], DFF, D_, 64, 224, CU_TENSOR_MAP_SWIZZLE_128B);
  Params p;
  p.x = (const __nv_bfloat16*)d_in[0]; p.wqkv = (const __nv_bfloat16*)d_in[1]; p.wo = (const __nv_bfloat16*)d_in[2]; p.w1 = (const __nv_bfloat16*)d_in[4];
  p.w2 = (const __nv_bfloat16*)d_in[5]; p.c = (const __nv_bfloat16*)d_in[6]; p.wmod = (const __nv_bfloat16*)d_in[7];
  p.out = (__nv_bfloat16*)d_out;
  cudaGetSymbolAddress((void**)&p.scr, g_scratch);
  cudaFuncSetAttribute(fused_block_kernel, cudaFuncAttributeMaxDynamicSharedMemorySize, SM_TOTAL);
  fused_block_kernel<<<128, 384, SM_TOTAL, cudaStreamPerThread>>>(tx, tqkv, two, tw1a, tw1b, tw2, txs, p);
}
```
